```python
import torch

def _softmax(x, axis=-1):
    return torch.softmax(x, dim=axis)

def _gelu(x):
    return torch.nn.functional.gelu(x, approximate='tanh')

def _silu(x):
    return torch.nn.functional.silu(x)

def _sigmoid(x):
    return torch.sigmoid(x)

def _layernorm(x, axis=-1, eps=1e-05):
    m = x.mean(dim=axis, keepdim=True)
    v = x.var(dim=axis, keepdim=True, unbiased=False)
    return (x - m) / torch.sqrt(v + eps)

def _scatter_add(tgt, idx, src, axis=0):
    return tgt.clone().index_add_(axis, idx, src)

def _segment_sum(src, seg, n):
    out = torch.zeros((n,) + src.shape[1:], dtype=src.dtype)
    return out.index_add_(0, seg, src)

def _pad(x, pw):
    flat = tuple((v for pair in reversed(pw) for v in pair))
    return torch.nn.functional.pad(x, flat)
kernel_name = 'adaLN_cond__ssm_conv_h3__glu_gated_reglu__prompt'

def setup_inputs():

    _w = lambda a: (lambda t: t.to(torch.bfloat16) if t.is_floating_point() else t)(torch.as_tensor(a))

    def _A_setup():
        B, S, D = (1, 2048, 640)
        ks = 4
        return {'q': _w((lambda *s: torch.randn(*s, dtype=torch.bfloat16) * 0.05)(B, S, D)), 'k': _w((lambda *s: torch.randn(*s, dtype=torch.bfloat16) * 0.8)(B, S, D)), 'v': _w((lambda *s: torch.randn(*s, dtype=torch.bfloat16) * 0.8)(B, S, D)), 'shift_k': _w((lambda *s: torch.randn(*s, dtype=torch.bfloat16) * 0.8)(D, ks) * 0.5), 'ssm_k': _w((lambda *s: torch.randn(*s, dtype=torch.bfloat16) * 0.8)(D, S) * (1.0 / S ** 0.5)), 'ssm_D': _w((lambda *s: torch.randn(*s, dtype=torch.bfloat16) * 0.8)(D))}
    _A_in = _A_setup()

    def _B_setup():
        B, S, D, F = (1, 2048, 640, 1536)
        return {'x': _w((lambda *s: torch.randn(*s, dtype=torch.bfloat16) * 0.05)(B, S, D)), 'W_gate': _w((lambda *s: torch.randn(*s, dtype=torch.bfloat16) * 0.8)(D, F) * (2.0 / D) ** 0.5), 'W_up': _w((lambda *s: torch.randn(*s, dtype=torch.bfloat16) * 0.8)(D, F) * (2.0 / D) ** 0.5), 'W_down': _w((lambda *s: torch.randn(*s, dtype=torch.bfloat16) * 0.8)(F, D) * (1.0 / F) ** 0.5)}
    _B_in = _B_setup()
    return {'A_q': _A_in['q'], 'A_k': _A_in['k'], 'A_v': _A_in['v'], 'A_shift_k': _A_in['shift_k'], 'A_ssm_k': _A_in['ssm_k'], 'A_ssm_D': _A_in['ssm_D'], 'B_x': _B_in['x'], 'B_W_gate': _B_in['W_gate'], 'B_W_up': _B_in['W_up'], 'B_W_down': _B_in['W_down'], 'c': _w((lambda *s: torch.randn(*s, dtype=torch.bfloat16) * 0.2)(1, 640) * 8.0), 'w_mod': _w((lambda *s: torch.randn(*s, dtype=torch.bfloat16) * 0.2)(640, 6 * 640) * 640 ** (-0.5) * 8.0)}

def reference(A_q, A_k, A_v, A_shift_k, A_ssm_k, A_ssm_D, B_x, B_W_gate, B_W_up, B_W_down, c, w_mod):

    def _A_ref(q, k, v, shift_k, ssm_k, ssm_D):
        B, S, D = q.shape
        ks = shift_k.shape[-1]
        k_pad = _pad(k, ((0, 0), (ks - 1, 0), (0, 0)))
        k_shift = torch.zeros_like(k)
        for t in range(ks):
            k_shift = k_shift + k_pad[:, t:t + S, :] * shift_k[:, ks - 1 - t][None, None, :]
        kv = k_shift * v
        L = 2 * S
        kv_pad = _pad(kv, ((0, 0), (0, S), (0, 0)))
        kf_pad = _pad(ssm_k, ((0, 0), (0, S)))
        kv_f = (lambda x, axes=(-2, -1): torch.fft.rfft2(x.float(), dim=axes))(kv_pad[:, None, :, :], axes=(1, 2))
        kf_f = (lambda x, axes=(-2, -1): torch.fft.rfft2(x.float(), dim=axes))(kf_pad[:, None, :], axes=(1, 2))
        kf_f = (lambda x, *d: x.permute(*d))(kf_f, 1, 2, 0)
        y_f = kv_f * kf_f[None, :, :, :]
        y = (lambda x, s, axes=(-2, -1): torch.fft.irfft2(x, s=s, dim=axes).to(torch.bfloat16))(y_f, (1, L), axes=(1, 2))[:, 0, :S, :]
        y = y + kv * ssm_D[None, None, :]
        return q * y

    def _B_ref(x, W_gate, W_up, W_down):
        gate = torch.einsum('bsd,df->bsf', x, W_gate)
        up = torch.einsum('bsd,df->bsf', x, W_up)
        gate = gate * (lambda x, dt: x.to(dt))(gate > 0, gate.dtype)
        h = gate * up
        return torch.einsum('bsf,fd->bsd', h, W_down)
    x = A_q
    mod = (_silu(c) @ w_mod).reshape(c.shape[0], 6, 1, -1)
    sa, ca, ga, sb, cb, gb = (mod[:, 0].clone(), mod[:, 1].clone(), mod[:, 2].clone(), mod[:, 3].clone(), mod[:, 4].clone(), mod[:, 5].clone())
    h = _layernorm(x, axis=-1) * (1 + ca) + sa
    x = x + ga * _A_ref(h, A_k, A_v, A_shift_k, A_ssm_k, A_ssm_D)
    h = _layernorm(x, axis=-1) * (1 + cb) + sb
    x = x + gb * _B_ref(h, B_W_gate, B_W_up, B_W_down)
    return x
```

```cpp
#include <cuda_runtime.h>
#include <cuda_bf16.h>
#include <cuda.h>
#include <stdint.h>
#include <stddef.h>
#include <type_traits>

namespace {

constexpr int S_ = 2048, D_ = 640;

struct Scratch {
    uint32_t cnt[8 * 2048];
    uint4 kvT[D_ * 256];
    uint4 yB[D_ * 256];
    uint4 z[D_ * 256];
    uint4 hh[16 * 24 * 1024];
    uint2 st1[128 * 64], st2[128 * 64];
    uint2 mod[3840];
    uint2 ut[5 * 3072];
};
__device__ __align__(8192) Scratch g_s;
#define SC(f, off) padd(P.scr, (uint32_t)offsetof(Scratch, f) + (off))
constexpr int C_KV = 0  , C_ZO = 31, C_Y = 64, C_Z = 128  , C_HH = 448  ;
#define GSTAMPIF(c, i) do {} while (0)
#define STAMPIF(c, i) do {} while (0)
#define STAMPL(c, i) do {} while (0)
#define PROF_EXIT() do {} while (0)
#define STAMP(i) do {} while (0)

constexpr uint32_t WR = 163840, MISC = 229376, SMEM_BYTES = 232448;
constexpr uint32_t XP = 4112, KVP = 8704, PP = 4352;
constexpr uint32_t SHT = 3 * KVP, KV3 = WR + 32768;
constexpr uint32_t HS = 32768, HO = HS + 20704, DS = HS + 28928;
constexpr uint32_t PB = 98304, XB = PB + 4 * PP;
constexpr uint32_t UST = 98304;
constexpr uint32_t QS = 131072, YS = QS + 20480;
__host__ __device__ constexpr uint32_t kv_at(int r) { return r * KVP + (r >= 3) * (KV3 - 3 * KVP); }
__host__ __device__ constexpr uint32_t x_at(int r) { return XB - (r & 1) * 32768 + (r >> 1) * XP; }
constexpr uint32_t BARS = MISC, HT = MISC + 680, TAB1 = MISC + 688, TAB2 = TAB1 + 32 * 48;
constexpr uint32_t CT = TAB1, MR = TAB1 + 512, CS_TAB = TAB1 + 768, PS = TAB1 + 1408, PRE = PS + 512;
constexpr uint32_t GBT = TAB1 + 64, G2B = 8192, G2A = 131072;
__host__ __device__ constexpr uint32_t g2b_at(int g) { return G2B + (g < 4 ? g + 2 : g - 4) * 20480; }
__host__ __device__ constexpr uint32_t w2_at(int it) { return it < 4 ? WR + it * 16384 : (it & 1) ? (it >> 1) * 16384 - 32768 : WR + (it >> 1) * 16384 - 32768; }
__host__ __device__ constexpr int w2_bar(int it);
enum { B_KV = 0, B_H = 5, B_Q = 10, B_XF = 15, B_YF = 20, B_AF = 25, B_WF = 35, B_G2F = 39, B_CR = 45, B_RT = 46, B_WE = 47, B_G2E = 51,
       B_S0 = 57, B_HD = 58, B_UD = 60, B_T1 = 61, B_FF = 62  , B_GO = 64, B_UF = 65, B_X1 = 66, B_FD = 67, B_WX = 72  , B_HE = 75  , NBARS = 78 };
__host__ __device__ constexpr uint32_t bar_count(int i) {
    return (i > B_XF && i < B_YF) ? 5 : i < B_WE ? 1 : i < B_S0 ? 16 : i < B_UD ? 8 : i == B_UD ? 9 : i == B_T1 ? 3 : i == B_X1 ? 1 : (i == B_FF + 1 || i == B_GO) ? 4 : i < B_WX ? 2 : i < B_HE ? 1 : 8;
}
__host__ __device__ constexpr int w2_bar(int it) { return it < 4 ? B_WF + it : ((it & 1) ? B_WX : B_WF) + (it >> 1) - 2; }
#define HPS 0xeca84310u
#define B2S 0xa88765
#define KB_UT 4
#define NPF 64
#define FA 24
#define MAP 2
#define FMAP 1
constexpr int NLD = 20;
struct Sched { uint32_t ld[NLD], wl[5], d_sp, d_w, g_w, xd, pw, spin, g_sp; };

__device__ __forceinline__ uint32_t smem_u32(const void* p) { return (uint32_t)__cvta_generic_to_shared(p); }
__device__ __forceinline__ void mbar_init(uint32_t bar, uint32_t cnt) { asm volatile("mbarrier.init.shared::cta.b64 [%0], %1;" :: "r"(bar), "r"(cnt) : "memory"); }
__device__ __forceinline__ void mbar_expect(uint32_t bar, uint32_t bytes) { asm volatile("mbarrier.arrive.expect_tx.shared::cta.b64 _, [%0], %1;" :: "r"(bar), "r"(bytes) : "memory"); }
__device__ __forceinline__ void mbar_arrive(uint32_t bar) { asm volatile("mbarrier.arrive.shared::cta.b64 _, [%0];" :: "r"(bar) : "memory"); }
__device__ __forceinline__ void mbar_arrive_if(uint32_t bar, bool p) { asm volatile("{ .reg .pred p; setp.ne.b32 p, %1, 0; @p mbarrier.arrive.shared::cta.b64 _, [%0]; }" :: "r"(bar), "r"((int)p) : "memory"); }
__device__ __forceinline__ void mbar_arrive_remote_if(uint32_t bar, bool p) { asm volatile("{ .reg .pred p; setp.ne.b32 p, %1, 0; @p mbarrier.arrive.shared::cluster.b64 _, [%0]; }" :: "r"(bar), "r"((int)p) : "memory"); }
__device__ __forceinline__ void mbar_wait(uint32_t bar, uint32_t parity) {
    asm volatile("{\n .reg .pred p, q; .reg .u32 c; mov.u32 c, 0;\n LAB_WAIT:\n mbarrier.try_wait.parity.shared::cta.b64 p, [%0], %1;\n @p bra LAB_DONE;\n"
                 " add.u32 c, c, 1; setp.lt.u32 q, c, 16384;\n @q bra LAB_WAIT;\n LAB_DONE:\n }" :: "r"(bar), "r"(parity) : "memory");
}
__device__ __forceinline__ bool mbar_test(uint32_t bar, uint32_t parity) {
    uint32_t ok; asm volatile("{ .reg .pred p; mbarrier.test_wait.parity.shared::cta.b64 p, [%1], %2; selp.u32 %0, 1, 0, p; }" : "=r"(ok) : "r"(bar), "r"(parity) : "memory"); return ok;
}
__device__ __forceinline__ void wait_clock(uint32_t t0, uint32_t d) {
    asm volatile("{\n .reg .pred p; .reg .u32 t;\n LAB_CLK:\n mov.u32 t, %%clock; sub.u32 t, t, %0; setp.lt.u32 p, t, %1;\n @p bra LAB_CLK;\n }" :: "r"(t0), "r"(d) : "memory");
}
__device__ __forceinline__ void pause(uint32_t d) { uint32_t t; asm volatile("mov.u32 %0, %%clock;" : "=r"(t)); wait_clock(t, d); }
__device__ __forceinline__ void mbar_wait_cluster(uint32_t bar, uint32_t parity) {
    asm volatile("{\n .reg .pred p, q; .reg .u32 c; mov.u32 c, 0;\n LAB_WAIT:\n mbarrier.try_wait.parity.acquire.cluster.shared::cta.b64 p, [%0], %1;\n @p bra LAB_DONE;\n"
                 " add.u32 c, c, 1; setp.lt.u32 q, c, 16384;\n @q bra LAB_WAIT;\n LAB_DONE:\n }" :: "r"(bar), "r"(parity) : "memory");
}
__device__ __forceinline__ bool elect() { uint32_t p; asm volatile("{ .reg .pred p; elect.sync _|p, 0xffffffff; selp.u32 %0, 1, 0, p; }" : "=r"(p)); return p; }
__device__ __forceinline__ void pf_map(const CUtensorMap* m) { asm volatile("prefetch.tensormap [%0];" :: "l"(m) : "memory"); }
__device__ __forceinline__ void bar_sync(int id, int n) { asm volatile("bar.sync %0, %1;" :: "r"(id), "r"(n) : "memory"); }
__device__ __forceinline__ void bar_arrive(int id, int n) { asm volatile("bar.arrive %0, %1;" :: "r"(id), "r"(n) : "memory"); }
__device__ __forceinline__ void fence_async_smem() { asm volatile("fence.proxy.async.shared::cta;" ::: "memory"); }
__device__ __forceinline__ void fence_async_glob() { asm volatile("fence.proxy.async.global;" ::: "memory"); }
__device__ __forceinline__ void bulk_g2s(uint32_t dst, const void* src, uint32_t bytes, uint32_t bar) {
    asm volatile("cp.async.bulk.shared::cluster.global.mbarrier::complete_tx::bytes [%0], [%1], %2, [%3];" :: "r"(dst), "l"(src), "r"(bytes), "r"(bar) : "memory");
}
__device__ __forceinline__ void pf_l2(const void* src, uint32_t bytes) { asm volatile("cp.async.bulk.prefetch.L2.global [%0], %1;" :: "l"(src), "r"(bytes) : "memory"); }
__device__ __forceinline__ void tma2d(uint32_t dst, const CUtensorMap* m, int c0, int c1, uint32_t bar) {
    asm volatile("cp.async.bulk.tensor.2d.shared::cluster.global.mbarrier::complete_tx::bytes [%0], [%1, {%3, %4}], [%2];" :: "r"(dst), "l"(m), "r"(bar), "r"(c0), "r"(c1) : "memory");
}
__device__ __forceinline__ void tma3d(uint32_t dst, const CUtensorMap* m, int c0, int c1, int c2, uint32_t bar) {
    asm volatile("cp.async.bulk.tensor.3d.shared::cluster.global.mbarrier::complete_tx::bytes [%0], [%1, {%3, %4, %5}], [%2];" :: "r"(dst), "l"(m), "r"(bar), "r"(c0), "r"(c1), "r"(c2) : "memory");
}
__device__ __forceinline__ void tma4d(uint32_t dst, const CUtensorMap* m, int c0, int c2, uint32_t bar) {
    asm volatile("cp.async.bulk.tensor.4d.shared::cluster.global.mbarrier::complete_tx::bytes [%0], [%1, {%3, %5, %4, %5}], [%2];" :: "r"(dst), "l"(m), "r"(bar), "r"(c0), "r"(c2), "r"(0) : "memory");
}
__device__ __forceinline__ void tma4d_st(const CUtensorMap* m, uint32_t src, int c0, int c2) {
    asm volatile("cp.async.bulk.tensor.4d.global.shared::cta.bulk_group [%0, {%2, %4, %3, %4}], [%1];" :: "l"(m), "r"(src), "r"(c0), "r"(c2), "r"(0) : "memory");
}
__device__ __forceinline__ void tma5d_mc(uint32_t dst, const CUtensorMap* m, int c2, int c4, uint32_t bar) {
    asm volatile("cp.async.bulk.tensor.5d.shared::cluster.global.mbarrier::complete_tx::bytes.multicast::cluster [%0], [%1, {%5, %5, %3, %5, %4}], [%2], %6;"
                 :: "r"(dst), "l"(m), "r"(bar), "r"(c2), "r"(c4), "r"(0), "h"((uint16_t)3) : "memory");
}
__device__ __forceinline__ void tma3d_mc(uint32_t dst, const CUtensorMap* m, int c1, int c2, uint32_t bar, uint16_t mask = 3) {
    asm volatile("cp.async.bulk.tensor.3d.shared::cluster.global.mbarrier::complete_tx::bytes.multicast::cluster [%0], [%1, {%5, %3, %4}], [%2], %6;"
                 :: "r"(dst), "l"(m), "r"(bar), "r"(c1), "r"(c2), "r"(0), "h"(mask) : "memory");
}
__device__ __forceinline__ void tma2d_red(const CUtensorMap* m, uint32_t src, int c0, int c1) {
    asm volatile("cp.reduce.async.bulk.tensor.2d.global.shared::cta.add.bulk_group [%0, {%2, %3}], [%1];" :: "l"(m), "r"(src), "r"(c0), "r"(c1) : "memory");
}
#define FENCE_REL "fence.release.gpu;"
__device__ __forceinline__ void signal_cnt(uint32_t* c, uint32_t inc) {
    asm volatile(FENCE_REL "\n fence.proxy.async.global;\n red.relaxed.gpu.global.add.u32 [%0], %1; red.relaxed.gpu.global.add.u32 [%0+4096], %1;" :: "l"(c), "r"(inc) : "memory");
}
template<int INC = 4> __device__ __forceinline__ void hint_cnt(void* c, bool p) { asm volatile("{ .reg .pred p; setp.ne.b32 p, %1, 0; @p red.relaxed.gpu.global.add.u32 [%0], %2; }" :: "l"(c), "r"((int)p), "n"(INC) : "memory"); }
__device__ __forceinline__ void pre_add(uint32_t a, bool p) { asm volatile("{ .reg .pred p; setp.ne.b32 p, %1, 0; @p red.shared.add.u32 [%0], 1; }" :: "r"(a), "r"((int)p) : "memory"); }
__device__ __forceinline__ uint32_t tagbit(uint32_t x, uint32_t tag) { uint32_t r; asm("lop3.b32 %0, %1, %2, 1, 0xd8;" : "=r"(r) : "r"(x), "r"(tag)); return r; }
__device__ __forceinline__ void stg_b128(void* p, uint32_t x, uint32_t y, uint32_t z, uint32_t w) {
    asm volatile("{ .reg .b64 a, b; .reg .b128 v; mov.b64 a, {%1, %2}; mov.b64 b, {%3, %4}; mov.b128 v, {a, b}; st.relaxed.gpu.global.b128 [%0], v; }" :: "l"(p), "r"(x), "r"(y), "r"(z), "r"(w) : "memory");
}
template<int OFF> __device__ __forceinline__ void stg_tag2(void* p, uint32_t x, uint32_t y, uint32_t z, uint32_t w, uint32_t x2, uint32_t y2, uint32_t z2, uint32_t w2, uint32_t tag) {
    asm volatile("{ .reg .b32 t, u; .reg .b64 a, b, c, d; .reg .b128 v, v2; lop3.b32 t, %1, %9, 1, 0xd8; lop3.b32 u, %5, %9, 1, 0xd8;\n"
                 " mov.b64 a, {t, %2}; mov.b64 b, {%3, %4}; mov.b128 v, {a, b}; mov.b64 c, {u, %6}; mov.b64 d, {%7, %8}; mov.b128 v2, {c, d};\n"
                 " st.relaxed.gpu.global.b128 [%0], v; st.relaxed.gpu.global.b128 [%0+%10], v2; }"
                 :: "l"(p), "r"(x), "r"(y), "r"(z), "r"(w), "r"(x2), "r"(y2), "r"(z2), "r"(w2), "r"(tag), "n"(OFF) : "memory");
}
__device__ __forceinline__ uint4 ldg_tag(const void* p, uint32_t tag) {
    uint4 v;
    _Pragma("unroll 1") for (int it = 0; it < 20000; it++) {
        asm volatile("{ .reg .b64 a, b; .reg .b128 v; ld.relaxed.gpu.global.b128 v, [%4]; mov.b128 {a, b}, v; mov.b64 {%0, %1}, a; mov.b64 {%2, %3}, b; }" : "=r"(v.x), "=r"(v.y), "=r"(v.z), "=r"(v.w) : "l"(p) : "memory");
        if (!((v.x ^ tag) & 1)) break;
    }
    return v;
}
__device__ __forceinline__ void poll_dual(const uint32_t* c, uint32_t slot, uint32_t d, uint32_t target) {
    asm volatile("{\n .reg .pred p, q; .reg .u32 n, v, w; mov.u32 n, 0;\n LAB_PD:\n ld.volatile.shared.u32 v, [%2]; ld.volatile.shared.u32 w, [%2+16];\n"
                 " sub.u32 v, v, %3; sub.u32 w, w, %3; and.b32 v, v, w; setp.ge.s32 p, v, 0;\n @p bra LAB_PDD;\n"
                 " cp.async.cg.shared.global [%1], [%0], 16; cp.async.cg.shared.global [%1+16], [%0+4096], 16; cp.async.commit_group; cp.async.wait_group 2;\n"
                 " add.u32 n, n, 1; setp.lt.u32 q, n, 100000;\n @q bra LAB_PD;\n LAB_PDD:\n }" :: "l"(c), "r"(slot), "r"(slot + d), "r"(target) : "memory");
}
__device__ __forceinline__ void poll_cnt(const uint32_t* c, uint32_t target) {
    asm volatile("{\n .reg .pred p, q; .reg .u32 c, v; mov.u32 c, 0;\n LAB_POLL:\n ld.relaxed.gpu.global.u32 v, [%0];\n sub.u32 v, v, %1; setp.ge.s32 p, v, 0;\n @p bra LAB_PDONE;\n"
                 " add.u32 c, c, 1; setp.lt.u32 q, c, 20000;\n @q bra LAB_POLL;\n LAB_PDONE:\n fence.acquire.gpu;\n }" :: "l"(c), "r"(target) : "memory");
}
template<int N1, int S1, int N2, int S2> __device__ __forceinline__ void ll_read2(const char* p, uint32_t tag, float2* out) {
    constexpr int N = N1 * N2;
    _Pragma("unroll 1") for (int it = 0; it < 20000; it++) {
        uint32_t a[N], b[N], t0[N], t1[N];
        #pragma unroll
        for (int i = 0; i < N; i++)
            asm volatile("{ .reg .b64 x, y; ld.relaxed.gpu.global.v2.b64 {x, y}, [%4]; mov.b64 {%0, %1}, x; mov.b64 {%2, %3}, y; }"
                         : "=r"(a[i]), "=r"(t0[i]), "=r"(b[i]), "=r"(t1[i]) : "l"(p + (i / N2) * S1 + (i % N2) * S2) : "memory");
        uint32_t bad = 0;
        #pragma unroll
        for (int i = 0; i < N; i++) { bad |= (t0[i] ^ tag) | (t1[i] ^ tag); out[i] = make_float2(__uint_as_float(a[i]), __uint_as_float(b[i])); }
        if (!__any_sync(~0u, bad != 0)) break;
        asm volatile("nanosleep.u32 200;");
    }
}
template<int N, int STRIDE> __device__ __forceinline__ void ll_read(const char* p, uint32_t tag, float2* out) { ll_read2<1, 0, N, STRIDE>(p, tag, out); }
__device__ __forceinline__ void ll_write1(void* p, float a, uint32_t tag) {
    asm volatile("{ .reg .b64 x; mov.b64 x, {%1, %2}; st.relaxed.gpu.global.b64 [%0], x; }" :: "l"(p), "r"(__float_as_uint(a)), "r"(tag) : "memory");
}
__device__ __forceinline__ uint4 lds128(uint32_t a) { uint4 v; asm volatile("ld.shared.v4.b32 {%0,%1,%2,%3}, [%4];" : "=r"(v.x), "=r"(v.y), "=r"(v.z), "=r"(v.w) : "r"(a) : "memory"); return v; }
__device__ __forceinline__ void sts128(uint32_t a, uint32_t x, uint32_t y, uint32_t z, uint32_t w) { asm volatile("st.shared.v4.b32 [%0], {%1,%2,%3,%4};" :: "r"(a), "r"(x), "r"(y), "r"(z), "r"(w) : "memory"); }
__device__ __forceinline__ void sts32(uint32_t a, uint32_t x) { asm volatile("st.shared.b32 [%0], %1;" :: "r"(a), "r"(x) : "memory"); }
__device__ __forceinline__ uint4 ldg_rlx128(const void* p) { uint4 v; asm volatile("{ .reg .b64 x, y; ld.relaxed.gpu.global.v2.b64 {x, y}, [%4]; mov.b64 {%0, %1}, x; mov.b64 {%2, %3}, y; }" : "=r"(v.x), "=r"(v.y), "=r"(v.z), "=r"(v.w) : "l"(p) : "memory"); return v; }
__device__ __forceinline__ uint32_t lds32(uint32_t a) { uint32_t v; asm volatile("ld.shared.b32 %0, [%1];" : "=r"(v) : "r"(a) : "memory"); return v; }
__device__ __forceinline__ void stg128(void* p, uint32_t x, uint32_t y, uint32_t z, uint32_t w) { asm volatile("st.global.v4.b32 [%0], {%1,%2,%3,%4};" :: "l"(p), "r"(x), "r"(y), "r"(z), "r"(w) : "memory"); }
__device__ __forceinline__ char* padd(const void* p, uint32_t off) { char* r; asm("{ .reg .u64 t; cvt.u64.u32 t, %2; add.u64 %0, %1, t; }" : "=l"(r) : "l"(p), "r"(off)); return r; }
__device__ __forceinline__ char* paddv(const void* p, uint32_t off) { char* r; asm volatile("{ .reg .u64 t; cvt.u64.u32 t, %2; add.u64 %0, %1, t; }" : "=l"(r) : "l"(p), "r"(off)); return r; }
__device__ __forceinline__ uint32_t prmt(uint32_t a, uint32_t b, uint32_t s) { uint32_t r; asm("prmt.b32 %0, %1, %2, %3;" : "=r"(r) : "r"(a), "r"(b), "r"(s)); return r; }
__device__ __forceinline__ uint32_t pack2(float lo, float hi) { uint32_t r; asm("cvt.rn.bf16x2.f32 %0, %1, %2;" : "=r"(r) : "f"(hi), "f"(lo)); return r; }
__device__ __forceinline__ uint32_t pack2relu(float lo, float hi) { uint32_t r; asm("cvt.rn.relu.bf16x2.f32 %0, %1, %2;" : "=r"(r) : "f"(hi), "f"(lo)); return r; }
__device__ __forceinline__ float bflo(uint32_t w) { return __uint_as_float(w << 16); }
__device__ __forceinline__ float bfhi(uint32_t w) { return __uint_as_float(w & 0xffff0000u); }
__device__ __forceinline__ float bfround(float x) { return bflo(pack2(x, x)); }
__device__ __forceinline__ uint32_t hmul2(uint32_t a, uint32_t b) { uint32_t r; asm("mul.rn.bf16x2 %0, %1, %2;" : "=r"(r) : "r"(a), "r"(b)); return r; }
__device__ __forceinline__ uint32_t hadd2(uint32_t a, uint32_t b) { uint32_t r; asm("add.rn.bf16x2 %0, %1, %2;" : "=r"(r) : "r"(a), "r"(b)); return r; }
__device__ __forceinline__ uint32_t hsub2(uint32_t a, uint32_t b) { uint32_t r; asm("sub.rn.bf16x2 %0, %1, %2;" : "=r"(r) : "r"(a), "r"(b)); return r; }
__device__ __forceinline__ uint32_t hfma2(uint32_t a, uint32_t b, uint32_t c) { uint32_t r; asm("fma.rn.bf16x2 %0, %1, %2, %3;" : "=r"(r) : "r"(a), "r"(b), "r"(c)); return r; }
__device__ __forceinline__ void wg_fence() { asm volatile("wgmma.fence.sync.aligned;" ::: "memory"); }
__device__ __forceinline__ void wg_commit() { asm volatile("wgmma.commit_group.sync.aligned;" ::: "memory"); }
template<int N> __device__ __forceinline__ void wg_wait() { asm volatile("wgmma.wait_group.sync.aligned %0;" :: "n"(N) : "memory"); }
template<int N> __device__ __forceinline__ void pin(float* d) {
    #pragma unroll
    for (int i = 0; i < N; i++) asm volatile("" : "+f"(d[i]) :: "memory");
}
__device__ __forceinline__ uint32_t dlo(uint32_t addr, uint32_t lbo) { return ((addr & 0x3FFFF) >> 4) | ((lbo >> 4) << 16); }
__host__ __device__ constexpr uint32_t dhi(uint32_t sbo, uint32_t sw) { return (sbo >> 4) | (sw << 30); }

template<int N> struct WG;
template<> struct WG<8> { template<int TA, int TB> static __device__ __forceinline__ void ss(float* d, uint32_t alo, uint32_t ahi, uint32_t blo, uint32_t bhi, int sd) {
  asm volatile("{ .reg .pred p; .reg .b64 da, db; mov.b64 da, {%4,%5}; mov.b64 db, {%6,%7}; setp.ne.b32 p, %8, 0;\n"
    "wgmma.mma_async.sync.aligned.m64n8k16.f32.bf16.bf16 {%0,%1,%2,%3}, da, db, p, 1, 1, %9, %10; }"
    : "+f"(d[0]),"+f"(d[1]),"+f"(d[2]),"+f"(d[3])
    : "r"(alo), "r"(ahi), "r"(blo), "r"(bhi), "r"(sd), "n"(TA), "n"(TB)); }
};
template<> struct WG<16> { template<int TA, int TB> static __device__ __forceinline__ void ss(float* d, uint32_t alo, uint32_t ahi, uint32_t blo, uint32_t bhi, int sd) {
  asm volatile("{ .reg .pred p; .reg .b64 da, db; mov.b64 da, {%8,%9}; mov.b64 db, {%10,%11}; setp.ne.b32 p, %12, 0;\n"
    "wgmma.mma_async.sync.aligned.m64n16k16.f32.bf16.bf16 {%0,%1,%2,%3,%4,%5,%6,%7}, da, db, p, 1, 1, %13, %14; }"
    : "+f"(d[0]),"+f"(d[1]),"+f"(d[2]),"+f"(d[3]),"+f"(d[4]),"+f"(d[5]),"+f"(d[6]),"+f"(d[7])
    : "r"(alo), "r"(ahi), "r"(blo), "r"(bhi), "r"(sd), "n"(TA), "n"(TB)); }
  template<int TB> static __device__ __forceinline__ void rs(float* d, uint32_t a0, uint32_t a1, uint32_t a2, uint32_t a3, uint32_t blo, uint32_t bhi, int sd) {
  asm volatile("{ .reg .pred p; .reg .b64 db; mov.b64 db, {%12,%13}; setp.ne.b32 p, %15, 0;\n"
    "wgmma.mma_async.sync.aligned.m64n16k16.f32.bf16.bf16 {%0,%1,%2,%3,%4,%5,%6,%7}, {%8,%9,%10,%11}, db, p, 1, 1, %14; }"
    : "+f"(d[0]),"+f"(d[1]),"+f"(d[2]),"+f"(d[3]),"+f"(d[4]),"+f"(d[5]),"+f"(d[6]),"+f"(d[7])
    : "r"(a0), "r"(a1), "r"(a2), "r"(a3), "r"(blo), "r"(bhi), "n"(TB), "r"(sd)); }
};
template<> struct WG<32> { template<int TA, int TB> static __device__ __forceinline__ void ss(float* d, uint32_t alo, uint32_t ahi, uint32_t blo, uint32_t bhi, int sd) {
  asm volatile("{ .reg .pred p; .reg .b64 da, db; mov.b64 da, {%16,%17}; mov.b64 db, {%18,%19}; setp.ne.b32 p, %20, 0;\n"
    "wgmma.mma_async.sync.aligned.m64n32k16.f32.bf16.bf16 {%0,%1,%2,%3,%4,%5,%6,%7,%8,%9,%10,%11,%12,%13,%14,%15}, da, db, p, 1, 1, %21, %22; }"
    : "+f"(d[0]),"+f"(d[1]),"+f"(d[2]),"+f"(d[3]),"+f"(d[4]),"+f"(d[5]),"+f"(d[6]),"+f"(d[7]),"+f"(d[8]),"+f"(d[9]),"+f"(d[10]),"+f"(d[11]),"+f"(d[12]),"+f"(d[13]),"+f"(d[14]),"+f"(d[15])
    : "r"(alo), "r"(ahi), "r"(blo), "r"(bhi), "r"(sd), "n"(TA), "n"(TB)); }
  template<int TB> static __device__ __forceinline__ void rs(float* d, uint32_t a0, uint32_t a1, uint32_t a2, uint32_t a3, uint32_t blo, uint32_t bhi, int sd) {
  asm volatile("{ .reg .pred p; .reg .b64 db; mov.b64 db, {%20,%21}; setp.ne.b32 p, %23, 0;\n"
    "wgmma.mma_async.sync.aligned.m64n32k16.f32.bf16.bf16 {%0,%1,%2,%3,%4,%5,%6,%7,%8,%9,%10,%11,%12,%13,%14,%15}, {%16,%17,%18,%19}, db, p, 1, 1, %22; }"
    : "+f"(d[0]),"+f"(d[1]),"+f"(d[2]),"+f"(d[3]),"+f"(d[4]),"+f"(d[5]),"+f"(d[6]),"+f"(d[7]),"+f"(d[8]),"+f"(d[9]),"+f"(d[10]),"+f"(d[11]),"+f"(d[12]),"+f"(d[13]),"+f"(d[14]),"+f"(d[15])
    : "r"(a0), "r"(a1), "r"(a2), "r"(a3), "r"(blo), "r"(bhi), "n"(TB), "r"(sd)); }
};
template<> struct WG<48> { template<int TA, int TB> static __device__ __forceinline__ void ss(float* d, uint32_t alo, uint32_t ahi, uint32_t blo, uint32_t bhi, int sd) {
  asm volatile("{ .reg .pred p; .reg .b64 da, db; mov.b64 da, {%24,%25}; mov.b64 db, {%26,%27}; setp.ne.b32 p, %28, 0;\n"
    "wgmma.mma_async.sync.aligned.m64n48k16.f32.bf16.bf16 {%0,%1,%2,%3,%4,%5,%6,%7,%8,%9,%10,%11,%12,%13,%14,%15,%16,%17,%18,%19,%20,%21,%22,%23}, da, db, p, 1, 1, %29, %30; }"
    : "+f"(d[0]),"+f"(d[1]),"+f"(d[2]),"+f"(d[3]),"+f"(d[4]),"+f"(d[5]),"+f"(d[6]),"+f"(d[7]),"+f"(d[8]),"+f"(d[9]),"+f"(d[10]),"+f"(d[11]),"+f"(d[12]),"+f"(d[13]),"+f"(d[14]),"+f"(d[15]),"+f"(d[16]),"+f"(d[17]),"+f"(d[18]),"+f"(d[19]),"+f"(d[20]),"+f"(d[21]),"+f"(d[22]),"+f"(d[23])
    : "r"(alo), "r"(ahi), "r"(blo), "r"(bhi), "r"(sd), "n"(TA), "n"(TB)); }
  template<int TB> static __device__ __forceinline__ void rs(float* d, uint32_t a0, uint32_t a1, uint32_t a2, uint32_t a3, uint32_t blo, uint32_t bhi, int sd) {
  asm volatile("{ .reg .pred p; .reg .b64 db; mov.b64 db, {%28,%29}; setp.ne.b32 p, %31, 0;\n"
    "wgmma.mma_async.sync.aligned.m64n48k16.f32.bf16.bf16 {%0,%1,%2,%3,%4,%5,%6,%7,%8,%9,%10,%11,%12,%13,%14,%15,%16,%17,%18,%19,%20,%21,%22,%23}, {%24,%25,%26,%27}, db, p, 1, 1, %30; }"
    : "+f"(d[0]),"+f"(d[1]),"+f"(d[2]),"+f"(d[3]),"+f"(d[4]),"+f"(d[5]),"+f"(d[6]),"+f"(d[7]),"+f"(d[8]),"+f"(d[9]),"+f"(d[10]),"+f"(d[11]),"+f"(d[12]),"+f"(d[13]),"+f"(d[14]),"+f"(d[15]),"+f"(d[16]),"+f"(d[17]),"+f"(d[18]),"+f"(d[19]),"+f"(d[20]),"+f"(d[21]),"+f"(d[22]),"+f"(d[23])
    : "r"(a0), "r"(a1), "r"(a2), "r"(a3), "r"(blo), "r"(bhi), "n"(TB), "r"(sd)); }
};
template<> struct WG<64> { template<int TA, int TB> static __device__ __forceinline__ void ss(float* d, uint32_t alo, uint32_t ahi, uint32_t blo, uint32_t bhi, int sd) {
  asm volatile("{ .reg .pred p; .reg .b64 da, db; mov.b64 da, {%32,%33}; mov.b64 db, {%34,%35}; setp.ne.b32 p, %36, 0;\n"
    "wgmma.mma_async.sync.aligned.m64n64k16.f32.bf16.bf16 {%0,%1,%2,%3,%4,%5,%6,%7,%8,%9,%10,%11,%12,%13,%14,%15,%16,%17,%18,%19,%20,%21,%22,%23,%24,%25,%26,%27,%28,%29,%30,%31}, da, db, p, 1, 1, %37, %38; }"
    : "+f"(d[0]),"+f"(d[1]),"+f"(d[2]),"+f"(d[3]),"+f"(d[4]),"+f"(d[5]),"+f"(d[6]),"+f"(d[7]),"+f"(d[8]),"+f"(d[9]),"+f"(d[10]),"+f"(d[11]),"+f"(d[12]),"+f"(d[13]),"+f"(d[14]),"+f"(d[15]),"+f"(d[16]),"+f"(d[17]),"+f"(d[18]),"+f"(d[19]),"+f"(d[20]),"+f"(d[21]),"+f"(d[22]),"+f"(d[23]),"+f"(d[24]),"+f"(d[25]),"+f"(d[26]),"+f"(d[27]),"+f"(d[28]),"+f"(d[29]),"+f"(d[30]),"+f"(d[31])
    : "r"(alo), "r"(ahi), "r"(blo), "r"(bhi), "r"(sd), "n"(TA), "n"(TB)); }
  template<int TB> static __device__ __forceinline__ void rs(float* d, uint32_t a0, uint32_t a1, uint32_t a2, uint32_t a3, uint32_t blo, uint32_t bhi, int sd) {
  asm volatile("{ .reg .pred p; .reg .b64 db; mov.b64 db, {%36,%37}; setp.ne.b32 p, %39, 0;\n"
    "wgmma.mma_async.sync.aligned.m64n64k16.f32.bf16.bf16 {%0,%1,%2,%3,%4,%5,%6,%7,%8,%9,%10,%11,%12,%13,%14,%15,%16,%17,%18,%19,%20,%21,%22,%23,%24,%25,%26,%27,%28,%29,%30,%31}, {%32,%33,%34,%35}, db, p, 1, 1, %38; }"
    : "+f"(d[0]),"+f"(d[1]),"+f"(d[2]),"+f"(d[3]),"+f"(d[4]),"+f"(d[5]),"+f"(d[6]),"+f"(d[7]),"+f"(d[8]),"+f"(d[9]),"+f"(d[10]),"+f"(d[11]),"+f"(d[12]),"+f"(d[13]),"+f"(d[14]),"+f"(d[15]),"+f"(d[16]),"+f"(d[17]),"+f"(d[18]),"+f"(d[19]),"+f"(d[20]),"+f"(d[21]),"+f"(d[22]),"+f"(d[23]),"+f"(d[24]),"+f"(d[25]),"+f"(d[26]),"+f"(d[27]),"+f"(d[28]),"+f"(d[29]),"+f"(d[30]),"+f"(d[31])
    : "r"(a0), "r"(a1), "r"(a2), "r"(a3), "r"(blo), "r"(bhi), "n"(TB), "r"(sd)); }
};
template<> struct WG<80> { template<int TA, int TB> static __device__ __forceinline__ void ss(float* d, uint32_t alo, uint32_t ahi, uint32_t blo, uint32_t bhi, int sd) {
  asm volatile("{ .reg .pred p; .reg .b64 da, db; mov.b64 da, {%40,%41}; mov.b64 db, {%42,%43}; setp.ne.b32 p, %44, 0;\n"
    "wgmma.mma_async.sync.aligned.m64n80k16.f32.bf16.bf16 {%0,%1,%2,%3,%4,%5,%6,%7,%8,%9,%10,%11,%12,%13,%14,%15,%16,%17,%18,%19,%20,%21,%22,%23,%24,%25,%26,%27,%28,%29,%30,%31,%32,%33,%34,%35,%36,%37,%38,%39}, da, db, p, 1, 1, %45, %46; }"
    : "+f"(d[0]),"+f"(d[1]),"+f"(d[2]),"+f"(d[3]),"+f"(d[4]),"+f"(d[5]),"+f"(d[6]),"+f"(d[7]),"+f"(d[8]),"+f"(d[9]),"+f"(d[10]),"+f"(d[11]),"+f"(d[12]),"+f"(d[13]),"+f"(d[14]),"+f"(d[15]),"+f"(d[16]),"+f"(d[17]),"+f"(d[18]),"+f"(d[19]),"+f"(d[20]),"+f"(d[21]),"+f"(d[22]),"+f"(d[23]),"+f"(d[24]),"+f"(d[25]),"+f"(d[26]),"+f"(d[27]),"+f"(d[28]),"+f"(d[29]),"+f"(d[30]),"+f"(d[31]),"+f"(d[32]),"+f"(d[33]),"+f"(d[34]),"+f"(d[35]),"+f"(d[36]),"+f"(d[37]),"+f"(d[38]),"+f"(d[39])
    : "r"(alo), "r"(ahi), "r"(blo), "r"(bhi), "r"(sd), "n"(TA), "n"(TB)); }
  template<int TB> static __device__ __forceinline__ void rs(float* d, uint32_t a0, uint32_t a1, uint32_t a2, uint32_t a3, uint32_t blo, uint32_t bhi, int sd) {
  asm volatile("{ .reg .pred p; .reg .b64 db; mov.b64 db, {%44,%45}; setp.ne.b32 p, %47, 0;\n"
    "wgmma.mma_async.sync.aligned.m64n80k16.f32.bf16.bf16 {%0,%1,%2,%3,%4,%5,%6,%7,%8,%9,%10,%11,%12,%13,%14,%15,%16,%17,%18,%19,%20,%21,%22,%23,%24,%25,%26,%27,%28,%29,%30,%31,%32,%33,%34,%35,%36,%37,%38,%39}, {%40,%41,%42,%43}, db, p, 1, 1, %46; }"
    : "+f"(d[0]),"+f"(d[1]),"+f"(d[2]),"+f"(d[3]),"+f"(d[4]),"+f"(d[5]),"+f"(d[6]),"+f"(d[7]),"+f"(d[8]),"+f"(d[9]),"+f"(d[10]),"+f"(d[11]),"+f"(d[12]),"+f"(d[13]),"+f"(d[14]),"+f"(d[15]),"+f"(d[16]),"+f"(d[17]),"+f"(d[18]),"+f"(d[19]),"+f"(d[20]),"+f"(d[21]),"+f"(d[22]),"+f"(d[23]),"+f"(d[24]),"+f"(d[25]),"+f"(d[26]),"+f"(d[27]),"+f"(d[28]),"+f"(d[29]),"+f"(d[30]),"+f"(d[31]),"+f"(d[32]),"+f"(d[33]),"+f"(d[34]),"+f"(d[35]),"+f"(d[36]),"+f"(d[37]),"+f"(d[38]),"+f"(d[39])
    : "r"(a0), "r"(a1), "r"(a2), "r"(a3), "r"(blo), "r"(bhi), "n"(TB), "r"(sd)); }
};
template<> struct WG<96> { template<int TA, int TB> static __device__ __forceinline__ void ss(float* d, uint32_t alo, uint32_t ahi, uint32_t blo, uint32_t bhi, int sd) {
  asm volatile("{ .reg .pred p; .reg .b64 da, db; mov.b64 da, {%48,%49}; mov.b64 db, {%50,%51}; setp.ne.b32 p, %52, 0;\n"
    "wgmma.mma_async.sync.aligned.m64n96k16.f32.bf16.bf16 {%0,%1,%2,%3,%4,%5,%6,%7,%8,%9,%10,%11,%12,%13,%14,%15,%16,%17,%18,%19,%20,%21,%22,%23,%24,%25,%26,%27,%28,%29,%30,%31,%32,%33,%34,%35,%36,%37,%38,%39,%40,%41,%42,%43,%44,%45,%46,%47}, da, db, p, 1, 1, %53, %54; }"
    : "+f"(d[0]),"+f"(d[1]),"+f"(d[2]),"+f"(d[3]),"+f"(d[4]),"+f"(d[5]),"+f"(d[6]),"+f"(d[7]),"+f"(d[8]),"+f"(d[9]),"+f"(d[10]),"+f"(d[11]),"+f"(d[12]),"+f"(d[13]),"+f"(d[14]),"+f"(d[15]),"+f"(d[16]),"+f"(d[17]),"+f"(d[18]),"+f"(d[19]),"+f"(d[20]),"+f"(d[21]),"+f"(d[22]),"+f"(d[23]),"+f"(d[24]),"+f"(d[25]),"+f"(d[26]),"+f"(d[27]),"+f"(d[28]),"+f"(d[29]),"+f"(d[30]),"+f"(d[31]),"+f"(d[32]),"+f"(d[33]),"+f"(d[34]),"+f"(d[35]),"+f"(d[36]),"+f"(d[37]),"+f"(d[38]),"+f"(d[39]),"+f"(d[40]),"+f"(d[41]),"+f"(d[42]),"+f"(d[43]),"+f"(d[44]),"+f"(d[45]),"+f"(d[46]),"+f"(d[47])
    : "r"(alo), "r"(ahi), "r"(blo), "r"(bhi), "r"(sd), "n"(TA), "n"(TB)); }
  template<int TB> static __device__ __forceinline__ void rs(float* d, uint32_t a0, uint32_t a1, uint32_t a2, uint32_t a3, uint32_t blo, uint32_t bhi, int sd) {
  asm volatile("{ .reg .pred p; .reg .b64 db; mov.b64 db, {%52,%53}; setp.ne.b32 p, %55, 0;\n"
    "wgmma.mma_async.sync.aligned.m64n96k16.f32.bf16.bf16 {%0,%1,%2,%3,%4,%5,%6,%7,%8,%9,%10,%11,%12,%13,%14,%15,%16,%17,%18,%19,%20,%21,%22,%23,%24,%25,%26,%27,%28,%29,%30,%31,%32,%33,%34,%35,%36,%37,%38,%39,%40,%41,%42,%43,%44,%45,%46,%47}, {%48,%49,%50,%51}, db, p, 1, 1, %54; }"
    : "+f"(d[0]),"+f"(d[1]),"+f"(d[2]),"+f"(d[3]),"+f"(d[4]),"+f"(d[5]),"+f"(d[6]),"+f"(d[7]),"+f"(d[8]),"+f"(d[9]),"+f"(d[10]),"+f"(d[11]),"+f"(d[12]),"+f"(d[13]),"+f"(d[14]),"+f"(d[15]),"+f"(d[16]),"+f"(d[17]),"+f"(d[18]),"+f"(d[19]),"+f"(d[20]),"+f"(d[21]),"+f"(d[22]),"+f"(d[23]),"+f"(d[24]),"+f"(d[25]),"+f"(d[26]),"+f"(d[27]),"+f"(d[28]),"+f"(d[29]),"+f"(d[30]),"+f"(d[31]),"+f"(d[32]),"+f"(d[33]),"+f"(d[34]),"+f"(d[35]),"+f"(d[36]),"+f"(d[37]),"+f"(d[38]),"+f"(d[39]),"+f"(d[40]),"+f"(d[41]),"+f"(d[42]),"+f"(d[43]),"+f"(d[44]),"+f"(d[45]),"+f"(d[46]),"+f"(d[47])
    : "r"(a0), "r"(a1), "r"(a2), "r"(a3), "r"(blo), "r"(bhi), "n"(TB), "r"(sd)); }
};
template<> struct WG<112> { template<int TA, int TB> static __device__ __forceinline__ void ss(float* d, uint32_t alo, uint32_t ahi, uint32_t blo, uint32_t bhi, int sd) {
  asm volatile("{ .reg .pred p; .reg .b64 da, db; mov.b64 da, {%56,%57}; mov.b64 db, {%58,%59}; setp.ne.b32 p, %60, 0;\n"
    "wgmma.mma_async.sync.aligned.m64n112k16.f32.bf16.bf16 {%0,%1,%2,%3,%4,%5,%6,%7,%8,%9,%10,%11,%12,%13,%14,%15,%16,%17,%18,%19,%20,%21,%22,%23,%24,%25,%26,%27,%28,%29,%30,%31,%32,%33,%34,%35,%36,%37,%38,%39,%40,%41,%42,%43,%44,%45,%46,%47,%48,%49,%50,%51,%52,%53,%54,%55}, da, db, p, 1, 1, %61, %62; }"
    : "+f"(d[0]),"+f"(d[1]),"+f"(d[2]),"+f"(d[3]),"+f"(d[4]),"+f"(d[5]),"+f"(d[6]),"+f"(d[7]),"+f"(d[8]),"+f"(d[9]),"+f"(d[10]),"+f"(d[11]),"+f"(d[12]),"+f"(d[13]),"+f"(d[14]),"+f"(d[15]),"+f"(d[16]),"+f"(d[17]),"+f"(d[18]),"+f"(d[19]),"+f"(d[20]),"+f"(d[21]),"+f"(d[22]),"+f"(d[23]),"+f"(d[24]),"+f"(d[25]),"+f"(d[26]),"+f"(d[27]),"+f"(d[28]),"+f"(d[29]),"+f"(d[30]),"+f"(d[31]),"+f"(d[32]),"+f"(d[33]),"+f"(d[34]),"+f"(d[35]),"+f"(d[36]),"+f"(d[37]),"+f"(d[38]),"+f"(d[39]),"+f"(d[40]),"+f"(d[41]),"+f"(d[42]),"+f"(d[43]),"+f"(d[44]),"+f"(d[45]),"+f"(d[46]),"+f"(d[47]),"+f"(d[48]),"+f"(d[49]),"+f"(d[50]),"+f"(d[51]),"+f"(d[52]),"+f"(d[53]),"+f"(d[54]),"+f"(d[55])
    : "r"(alo), "r"(ahi), "r"(blo), "r"(bhi), "r"(sd), "n"(TA), "n"(TB)); }
  template<int TB> static __device__ __forceinline__ void rs(float* d, uint32_t a0, uint32_t a1, uint32_t a2, uint32_t a3, uint32_t blo, uint32_t bhi, int sd) {
  asm volatile("{ .reg .pred p; .reg .b64 db; mov.b64 db, {%60,%61}; setp.ne.b32 p, %63, 0;\n"
    "wgmma.mma_async.sync.aligned.m64n112k16.f32.bf16.bf16 {%0,%1,%2,%3,%4,%5,%6,%7,%8,%9,%10,%11,%12,%13,%14,%15,%16,%17,%18,%19,%20,%21,%22,%23,%24,%25,%26,%27,%28,%29,%30,%31,%32,%33,%34,%35,%36,%37,%38,%39,%40,%41,%42,%43,%44,%45,%46,%47,%48,%49,%50,%51,%52,%53,%54,%55}, {%56,%57,%58,%59}, db, p, 1, 1, %62; }"
    : "+f"(d[0]),"+f"(d[1]),"+f"(d[2]),"+f"(d[3]),"+f"(d[4]),"+f"(d[5]),"+f"(d[6]),"+f"(d[7]),"+f"(d[8]),"+f"(d[9]),"+f"(d[10]),"+f"(d[11]),"+f"(d[12]),"+f"(d[13]),"+f"(d[14]),"+f"(d[15]),"+f"(d[16]),"+f"(d[17]),"+f"(d[18]),"+f"(d[19]),"+f"(d[20]),"+f"(d[21]),"+f"(d[22]),"+f"(d[23]),"+f"(d[24]),"+f"(d[25]),"+f"(d[26]),"+f"(d[27]),"+f"(d[28]),"+f"(d[29]),"+f"(d[30]),"+f"(d[31]),"+f"(d[32]),"+f"(d[33]),"+f"(d[34]),"+f"(d[35]),"+f"(d[36]),"+f"(d[37]),"+f"(d[38]),"+f"(d[39]),"+f"(d[40]),"+f"(d[41]),"+f"(d[42]),"+f"(d[43]),"+f"(d[44]),"+f"(d[45]),"+f"(d[46]),"+f"(d[47]),"+f"(d[48]),"+f"(d[49]),"+f"(d[50]),"+f"(d[51]),"+f"(d[52]),"+f"(d[53]),"+f"(d[54]),"+f"(d[55])
    : "r"(a0), "r"(a1), "r"(a2), "r"(a3), "r"(blo), "r"(bhi), "n"(TB), "r"(sd)); }
};
template<> struct WG<128> { template<int TA, int TB> static __device__ __forceinline__ void ss(float* d, uint32_t alo, uint32_t ahi, uint32_t blo, uint32_t bhi, int sd) {
  asm volatile("{ .reg .pred p; .reg .b64 da, db; mov.b64 da, {%64,%65}; mov.b64 db, {%66,%67}; setp.ne.b32 p, %68, 0;\n"
    "wgmma.mma_async.sync.aligned.m64n128k16.f32.bf16.bf16 {%0,%1,%2,%3,%4,%5,%6,%7,%8,%9,%10,%11,%12,%13,%14,%15,%16,%17,%18,%19,%20,%21,%22,%23,%24,%25,%26,%27,%28,%29,%30,%31,%32,%33,%34,%35,%36,%37,%38,%39,%40,%41,%42,%43,%44,%45,%46,%47,%48,%49,%50,%51,%52,%53,%54,%55,%56,%57,%58,%59,%60,%61,%62,%63}, da, db, p, 1, 1, %69, %70; }"
    : "+f"(d[0]),"+f"(d[1]),"+f"(d[2]),"+f"(d[3]),"+f"(d[4]),"+f"(d[5]),"+f"(d[6]),"+f"(d[7]),"+f"(d[8]),"+f"(d[9]),"+f"(d[10]),"+f"(d[11]),"+f"(d[12]),"+f"(d[13]),"+f"(d[14]),"+f"(d[15]),"+f"(d[16]),"+f"(d[17]),"+f"(d[18]),"+f"(d[19]),"+f"(d[20]),"+f"(d[21]),"+f"(d[22]),"+f"(d[23]),"+f"(d[24]),"+f"(d[25]),"+f"(d[26]),"+f"(d[27]),"+f"(d[28]),"+f"(d[29]),"+f"(d[30]),"+f"(d[31]),"+f"(d[32]),"+f"(d[33]),"+f"(d[34]),"+f"(d[35]),"+f"(d[36]),"+f"(d[37]),"+f"(d[38]),"+f"(d[39]),"+f"(d[40]),"+f"(d[41]),"+f"(d[42]),"+f"(d[43]),"+f"(d[44]),"+f"(d[45]),"+f"(d[46]),"+f"(d[47]),"+f"(d[48]),"+f"(d[49]),"+f"(d[50]),"+f"(d[51]),"+f"(d[52]),"+f"(d[53]),"+f"(d[54]),"+f"(d[55]),"+f"(d[56]),"+f"(d[57]),"+f"(d[58]),"+f"(d[59]),"+f"(d[60]),"+f"(d[61]),"+f"(d[62]),"+f"(d[63])
    : "r"(alo), "r"(ahi), "r"(blo), "r"(bhi), "r"(sd), "n"(TA), "n"(TB)); }
  template<int TB> static __device__ __forceinline__ void rs(float* d, uint32_t a0, uint32_t a1, uint32_t a2, uint32_t a3, uint32_t blo, uint32_t bhi, int sd) {
  asm volatile("{ .reg .pred p; .reg .b64 db; mov.b64 db, {%68,%69}; setp.ne.b32 p, %71, 0;\n"
    "wgmma.mma_async.sync.aligned.m64n128k16.f32.bf16.bf16 {%0,%1,%2,%3,%4,%5,%6,%7,%8,%9,%10,%11,%12,%13,%14,%15,%16,%17,%18,%19,%20,%21,%22,%23,%24,%25,%26,%27,%28,%29,%30,%31,%32,%33,%34,%35,%36,%37,%38,%39,%40,%41,%42,%43,%44,%45,%46,%47,%48,%49,%50,%51,%52,%53,%54,%55,%56,%57,%58,%59,%60,%61,%62,%63}, {%64,%65,%66,%67}, db, p, 1, 1, %70; }"
    : "+f"(d[0]),"+f"(d[1]),"+f"(d[2]),"+f"(d[3]),"+f"(d[4]),"+f"(d[5]),"+f"(d[6]),"+f"(d[7]),"+f"(d[8]),"+f"(d[9]),"+f"(d[10]),"+f"(d[11]),"+f"(d[12]),"+f"(d[13]),"+f"(d[14]),"+f"(d[15]),"+f"(d[16]),"+f"(d[17]),"+f"(d[18]),"+f"(d[19]),"+f"(d[20]),"+f"(d[21]),"+f"(d[22]),"+f"(d[23]),"+f"(d[24]),"+f"(d[25]),"+f"(d[26]),"+f"(d[27]),"+f"(d[28]),"+f"(d[29]),"+f"(d[30]),"+f"(d[31]),"+f"(d[32]),"+f"(d[33]),"+f"(d[34]),"+f"(d[35]),"+f"(d[36]),"+f"(d[37]),"+f"(d[38]),"+f"(d[39]),"+f"(d[40]),"+f"(d[41]),"+f"(d[42]),"+f"(d[43]),"+f"(d[44]),"+f"(d[45]),"+f"(d[46]),"+f"(d[47]),"+f"(d[48]),"+f"(d[49]),"+f"(d[50]),"+f"(d[51]),"+f"(d[52]),"+f"(d[53]),"+f"(d[54]),"+f"(d[55]),"+f"(d[56]),"+f"(d[57]),"+f"(d[58]),"+f"(d[59]),"+f"(d[60]),"+f"(d[61]),"+f"(d[62]),"+f"(d[63])
    : "r"(a0), "r"(a1), "r"(a2), "r"(a3), "r"(blo), "r"(bhi), "n"(TB), "r"(sd)); }
};
template<> struct WG<144> { template<int TA, int TB> static __device__ __forceinline__ void ss(float* d, uint32_t alo, uint32_t ahi, uint32_t blo, uint32_t bhi, int sd) {
  asm volatile("{ .reg .pred p; .reg .b64 da, db; mov.b64 da, {%72,%73}; mov.b64 db, {%74,%75}; setp.ne.b32 p, %76, 0;\n"
    "wgmma.mma_async.sync.aligned.m64n144k16.f32.bf16.bf16 {%0,%1,%2,%3,%4,%5,%6,%7,%8,%9,%10,%11,%12,%13,%14,%15,%16,%17,%18,%19,%20,%21,%22,%23,%24,%25,%26,%27,%28,%29,%30,%31,%32,%33,%34,%35,%36,%37,%38,%39,%40,%41,%42,%43,%44,%45,%46,%47,%48,%49,%50,%51,%52,%53,%54,%55,%56,%57,%58,%59,%60,%61,%62,%63,%64,%65,%66,%67,%68,%69,%70,%71}, da, db, p, 1, 1, %77, %78; }"
    : "+f"(d[0]),"+f"(d[1]),"+f"(d[2]),"+f"(d[3]),"+f"(d[4]),"+f"(d[5]),"+f"(d[6]),"+f"(d[7]),"+f"(d[8]),"+f"(d[9]),"+f"(d[10]),"+f"(d[11]),"+f"(d[12]),"+f"(d[13]),"+f"(d[14]),"+f"(d[15]),"+f"(d[16]),"+f"(d[17]),"+f"(d[18]),"+f"(d[19]),"+f"(d[20]),"+f"(d[21]),"+f"(d[22]),"+f"(d[23]),"+f"(d[24]),"+f"(d[25]),"+f"(d[26]),"+f"(d[27]),"+f"(d[28]),"+f"(d[29]),"+f"(d[30]),"+f"(d[31]),"+f"(d[32]),"+f"(d[33]),"+f"(d[34]),"+f"(d[35]),"+f"(d[36]),"+f"(d[37]),"+f"(d[38]),"+f"(d[39]),"+f"(d[40]),"+f"(d[41]),"+f"(d[42]),"+f"(d[43]),"+f"(d[44]),"+f"(d[45]),"+f"(d[46]),"+f"(d[47]),"+f"(d[48]),"+f"(d[49]),"+f"(d[50]),"+f"(d[51]),"+f"(d[52]),"+f"(d[53]),"+f"(d[54]),"+f"(d[55]),"+f"(d[56]),"+f"(d[57]),"+f"(d[58]),"+f"(d[59]),"+f"(d[60]),"+f"(d[61]),"+f"(d[62]),"+f"(d[63]),"+f"(d[64]),"+f"(d[65]),"+f"(d[66]),"+f"(d[67]),"+f"(d[68]),"+f"(d[69]),"+f"(d[70]),"+f"(d[71])
    : "r"(alo), "r"(ahi), "r"(blo), "r"(bhi), "r"(sd), "n"(TA), "n"(TB)); }
  template<int TB> static __device__ __forceinline__ void rs(float* d, uint32_t a0, uint32_t a1, uint32_t a2, uint32_t a3, uint32_t blo, uint32_t bhi, int sd) {
  asm volatile("{ .reg .pred p; .reg .b64 db; mov.b64 db, {%76,%77}; setp.ne.b32 p, %79, 0;\n"
    "wgmma.mma_async.sync.aligned.m64n144k16.f32.bf16.bf16 {%0,%1,%2,%3,%4,%5,%6,%7,%8,%9,%10,%11,%12,%13,%14,%15,%16,%17,%18,%19,%20,%21,%22,%23,%24,%25,%26,%27,%28,%29,%30,%31,%32,%33,%34,%35,%36,%37,%38,%39,%40,%41,%42,%43,%44,%45,%46,%47,%48,%49,%50,%51,%52,%53,%54,%55,%56,%57,%58,%59,%60,%61,%62,%63,%64,%65,%66,%67,%68,%69,%70,%71}, {%72,%73,%74,%75}, db, p, 1, 1, %78; }"
    : "+f"(d[0]),"+f"(d[1]),"+f"(d[2]),"+f"(d[3]),"+f"(d[4]),"+f"(d[5]),"+f"(d[6]),"+f"(d[7]),"+f"(d[8]),"+f"(d[9]),"+f"(d[10]),"+f"(d[11]),"+f"(d[12]),"+f"(d[13]),"+f"(d[14]),"+f"(d[15]),"+f"(d[16]),"+f"(d[17]),"+f"(d[18]),"+f"(d[19]),"+f"(d[20]),"+f"(d[21]),"+f"(d[22]),"+f"(d[23]),"+f"(d[24]),"+f"(d[25]),"+f"(d[26]),"+f"(d[27]),"+f"(d[28]),"+f"(d[29]),"+f"(d[30]),"+f"(d[31]),"+f"(d[32]),"+f"(d[33]),"+f"(d[34]),"+f"(d[35]),"+f"(d[36]),"+f"(d[37]),"+f"(d[38]),"+f"(d[39]),"+f"(d[40]),"+f"(d[41]),"+f"(d[42]),"+f"(d[43]),"+f"(d[44]),"+f"(d[45]),"+f"(d[46]),"+f"(d[47]),"+f"(d[48]),"+f"(d[49]),"+f"(d[50]),"+f"(d[51]),"+f"(d[52]),"+f"(d[53]),"+f"(d[54]),"+f"(d[55]),"+f"(d[56]),"+f"(d[57]),"+f"(d[58]),"+f"(d[59]),"+f"(d[60]),"+f"(d[61]),"+f"(d[62]),"+f"(d[63]),"+f"(d[64]),"+f"(d[65]),"+f"(d[66]),"+f"(d[67]),"+f"(d[68]),"+f"(d[69]),"+f"(d[70]),"+f"(d[71])
    : "r"(a0), "r"(a1), "r"(a2), "r"(a3), "r"(blo), "r"(bhi), "n"(TB), "r"(sd)); }
};
template<> struct WG<160> { template<int TA, int TB> static __device__ __forceinline__ void ss(float* d, uint32_t alo, uint32_t ahi, uint32_t blo, uint32_t bhi, int sd) {
  asm volatile("{ .reg .pred p; .reg .b64 da, db; mov.b64 da, {%80,%81}; mov.b64 db, {%82,%83}; setp.ne.b32 p, %84, 0;\n"
    "wgmma.mma_async.sync.aligned.m64n160k16.f32.bf16.bf16 {%0,%1,%2,%3,%4,%5,%6,%7,%8,%9,%10,%11,%12,%13,%14,%15,%16,%17,%18,%19,%20,%21,%22,%23,%24,%25,%26,%27,%28,%29,%30,%31,%32,%33,%34,%35,%36,%37,%38,%39,%40,%41,%42,%43,%44,%45,%46,%47,%48,%49,%50,%51,%52,%53,%54,%55,%56,%57,%58,%59,%60,%61,%62,%63,%64,%65,%66,%67,%68,%69,%70,%71,%72,%73,%74,%75,%76,%77,%78,%79}, da, db, p, 1, 1, %85, %86; }"
    : "+f"(d[0]),"+f"(d[1]),"+f"(d[2]),"+f"(d[3]),"+f"(d[4]),"+f"(d[5]),"+f"(d[6]),"+f"(d[7]),"+f"(d[8]),"+f"(d[9]),"+f"(d[10]),"+f"(d[11]),"+f"(d[12]),"+f"(d[13]),"+f"(d[14]),"+f"(d[15]),"+f"(d[16]),"+f"(d[17]),"+f"(d[18]),"+f"(d[19]),"+f"(d[20]),"+f"(d[21]),"+f"(d[22]),"+f"(d[23]),"+f"(d[24]),"+f"(d[25]),"+f"(d[26]),"+f"(d[27]),"+f"(d[28]),"+f"(d[29]),"+f"(d[30]),"+f"(d[31]),"+f"(d[32]),"+f"(d[33]),"+f"(d[34]),"+f"(d[35]),"+f"(d[36]),"+f"(d[37]),"+f"(d[38]),"+f"(d[39]),"+f"(d[40]),"+f"(d[41]),"+f"(d[42]),"+f"(d[43]),"+f"(d[44]),"+f"(d[45]),"+f"(d[46]),"+f"(d[47]),"+f"(d[48]),"+f"(d[49]),"+f"(d[50]),"+f"(d[51]),"+f"(d[52]),"+f"(d[53]),"+f"(d[54]),"+f"(d[55]),"+f"(d[56]),"+f"(d[57]),"+f"(d[58]),"+f"(d[59]),"+f"(d[60]),"+f"(d[61]),"+f"(d[62]),"+f"(d[63]),"+f"(d[64]),"+f"(d[65]),"+f"(d[66]),"+f"(d[67]),"+f"(d[68]),"+f"(d[69]),"+f"(d[70]),"+f"(d[71]),"+f"(d[72]),"+f"(d[73]),"+f"(d[74]),"+f"(d[75]),"+f"(d[76]),"+f"(d[77]),"+f"(d[78]),"+f"(d[79])
    : "r"(alo), "r"(ahi), "r"(blo), "r"(bhi), "r"(sd), "n"(TA), "n"(TB)); }
  template<int TB> static __device__ __forceinline__ void rs(float* d, uint32_t a0, uint32_t a1, uint32_t a2, uint32_t a3, uint32_t blo, uint32_t bhi, int sd) {
  asm volatile("{ .reg .pred p; .reg .b64 db; mov.b64 db, {%84,%85}; setp.ne.b32 p, %87, 0;\n"
    "wgmma.mma_async.sync.aligned.m64n160k16.f32.bf16.bf16 {%0,%1,%2,%3,%4,%5,%6,%7,%8,%9,%10,%11,%12,%13,%14,%15,%16,%17,%18,%19,%20,%21,%22,%23,%24,%25,%26,%27,%28,%29,%30,%31,%32,%33,%34,%35,%36,%37,%38,%39,%40,%41,%42,%43,%44,%45,%46,%47,%48,%49,%50,%51,%52,%53,%54,%55,%56,%57,%58,%59,%60,%61,%62,%63,%64,%65,%66,%67,%68,%69,%70,%71,%72,%73,%74,%75,%76,%77,%78,%79}, {%80,%81,%82,%83}, db, p, 1, 1, %86; }"
    : "+f"(d[0]),"+f"(d[1]),"+f"(d[2]),"+f"(d[3]),"+f"(d[4]),"+f"(d[5]),"+f"(d[6]),"+f"(d[7]),"+f"(d[8]),"+f"(d[9]),"+f"(d[10]),"+f"(d[11]),"+f"(d[12]),"+f"(d[13]),"+f"(d[14]),"+f"(d[15]),"+f"(d[16]),"+f"(d[17]),"+f"(d[18]),"+f"(d[19]),"+f"(d[20]),"+f"(d[21]),"+f"(d[22]),"+f"(d[23]),"+f"(d[24]),"+f"(d[25]),"+f"(d[26]),"+f"(d[27]),"+f"(d[28]),"+f"(d[29]),"+f"(d[30]),"+f"(d[31]),"+f"(d[32]),"+f"(d[33]),"+f"(d[34]),"+f"(d[35]),"+f"(d[36]),"+f"(d[37]),"+f"(d[38]),"+f"(d[39]),"+f"(d[40]),"+f"(d[41]),"+f"(d[42]),"+f"(d[43]),"+f"(d[44]),"+f"(d[45]),"+f"(d[46]),"+f"(d[47]),"+f"(d[48]),"+f"(d[49]),"+f"(d[50]),"+f"(d[51]),"+f"(d[52]),"+f"(d[53]),"+f"(d[54]),"+f"(d[55]),"+f"(d[56]),"+f"(d[57]),"+f"(d[58]),"+f"(d[59]),"+f"(d[60]),"+f"(d[61]),"+f"(d[62]),"+f"(d[63]),"+f"(d[64]),"+f"(d[65]),"+f"(d[66]),"+f"(d[67]),"+f"(d[68]),"+f"(d[69]),"+f"(d[70]),"+f"(d[71]),"+f"(d[72]),"+f"(d[73]),"+f"(d[74]),"+f"(d[75]),"+f"(d[76]),"+f"(d[77]),"+f"(d[78]),"+f"(d[79])
    : "r"(a0), "r"(a1), "r"(a2), "r"(a3), "r"(blo), "r"(bhi), "n"(TB), "r"(sd)); }
};
template<> struct WG<176> { template<int TA, int TB> static __device__ __forceinline__ void ss(float* d, uint32_t alo, uint32_t ahi, uint32_t blo, uint32_t bhi, int sd) {
  asm volatile("{ .reg .pred p; .reg .b64 da, db; mov.b64 da, {%88,%89}; mov.b64 db, {%90,%91}; setp.ne.b32 p, %92, 0;\n"
    "wgmma.mma_async.sync.aligned.m64n176k16.f32.bf16.bf16 {%0,%1,%2,%3,%4,%5,%6,%7,%8,%9,%10,%11,%12,%13,%14,%15,%16,%17,%18,%19,%20,%21,%22,%23,%24,%25,%26,%27,%28,%29,%30,%31,%32,%33,%34,%35,%36,%37,%38,%39,%40,%41,%42,%43,%44,%45,%46,%47,%48,%49,%50,%51,%52,%53,%54,%55,%56,%57,%58,%59,%60,%61,%62,%63,%64,%65,%66,%67,%68,%69,%70,%71,%72,%73,%74,%75,%76,%77,%78,%79,%80,%81,%82,%83,%84,%85,%86,%87}, da, db, p, 1, 1, %93, %94; }"
    : "+f"(d[0]),"+f"(d[1]),"+f"(d[2]),"+f"(d[3]),"+f"(d[4]),"+f"(d[5]),"+f"(d[6]),"+f"(d[7]),"+f"(d[8]),"+f"(d[9]),"+f"(d[10]),"+f"(d[11]),"+f"(d[12]),"+f"(d[13]),"+f"(d[14]),"+f"(d[15]),"+f"(d[16]),"+f"(d[17]),"+f"(d[18]),"+f"(d[19]),"+f"(d[20]),"+f"(d[21]),"+f"(d[22]),"+f"(d[23]),"+f"(d[24]),"+f"(d[25]),"+f"(d[26]),"+f"(d[27]),"+f"(d[28]),"+f"(d[29]),"+f"(d[30]),"+f"(d[31]),"+f"(d[32]),"+f"(d[33]),"+f"(d[34]),"+f"(d[35]),"+f"(d[36]),"+f"(d[37]),"+f"(d[38]),"+f"(d[39]),"+f"(d[40]),"+f"(d[41]),"+f"(d[42]),"+f"(d[43]),"+f"(d[44]),"+f"(d[45]),"+f"(d[46]),"+f"(d[47]),"+f"(d[48]),"+f"(d[49]),"+f"(d[50]),"+f"(d[51]),"+f"(d[52]),"+f"(d[53]),"+f"(d[54]),"+f"(d[55]),"+f"(d[56]),"+f"(d[57]),"+f"(d[58]),"+f"(d[59]),"+f"(d[60]),"+f"(d[61]),"+f"(d[62]),"+f"(d[63]),"+f"(d[64]),"+f"(d[65]),"+f"(d[66]),"+f"(d[67]),"+f"(d[68]),"+f"(d[69]),"+f"(d[70]),"+f"(d[71]),"+f"(d[72]),"+f"(d[73]),"+f"(d[74]),"+f"(d[75]),"+f"(d[76]),"+f"(d[77]),"+f"(d[78]),"+f"(d[79]),"+f"(d[80]),"+f"(d[81]),"+f"(d[82]),"+f"(d[83]),"+f"(d[84]),"+f"(d[85]),"+f"(d[86]),"+f"(d[87])
    : "r"(alo), "r"(ahi), "r"(blo), "r"(bhi), "r"(sd), "n"(TA), "n"(TB)); }
  template<int TB> static __device__ __forceinline__ void rs(float* d, uint32_t a0, uint32_t a1, uint32_t a2, uint32_t a3, uint32_t blo, uint32_t bhi, int sd) {
  asm volatile("{ .reg .pred p; .reg .b64 db; mov.b64 db, {%92,%93}; setp.ne.b32 p, %95, 0;\n"
    "wgmma.mma_async.sync.aligned.m64n176k16.f32.bf16.bf16 {%0,%1,%2,%3,%4,%5,%6,%7,%8,%9,%10,%11,%12,%13,%14,%15,%16,%17,%18,%19,%20,%21,%22,%23,%24,%25,%26,%27,%28,%29,%30,%31,%32,%33,%34,%35,%36,%37,%38,%39,%40,%41,%42,%43,%44,%45,%46,%47,%48,%49,%50,%51,%52,%53,%54,%55,%56,%57,%58,%59,%60,%61,%62,%63,%64,%65,%66,%67,%68,%69,%70,%71,%72,%73,%74,%75,%76,%77,%78,%79,%80,%81,%82,%83,%84,%85,%86,%87}, {%88,%89,%90,%91}, db, p, 1, 1, %94; }"
    : "+f"(d[0]),"+f"(d[1]),"+f"(d[2]),"+f"(d[3]),"+f"(d[4]),"+f"(d[5]),"+f"(d[6]),"+f"(d[7]),"+f"(d[8]),"+f"(d[9]),"+f"(d[10]),"+f"(d[11]),"+f"(d[12]),"+f"(d[13]),"+f"(d[14]),"+f"(d[15]),"+f"(d[16]),"+f"(d[17]),"+f"(d[18]),"+f"(d[19]),"+f"(d[20]),"+f"(d[21]),"+f"(d[22]),"+f"(d[23]),"+f"(d[24]),"+f"(d[25]),"+f"(d[26]),"+f"(d[27]),"+f"(d[28]),"+f"(d[29]),"+f"(d[30]),"+f"(d[31]),"+f"(d[32]),"+f"(d[33]),"+f"(d[34]),"+f"(d[35]),"+f"(d[36]),"+f"(d[37]),"+f"(d[38]),"+f"(d[39]),"+f"(d[40]),"+f"(d[41]),"+f"(d[42]),"+f"(d[43]),"+f"(d[44]),"+f"(d[45]),"+f"(d[46]),"+f"(d[47]),"+f"(d[48]),"+f"(d[49]),"+f"(d[50]),"+f"(d[51]),"+f"(d[52]),"+f"(d[53]),"+f"(d[54]),"+f"(d[55]),"+f"(d[56]),"+f"(d[57]),"+f"(d[58]),"+f"(d[59]),"+f"(d[60]),"+f"(d[61]),"+f"(d[62]),"+f"(d[63]),"+f"(d[64]),"+f"(d[65]),"+f"(d[66]),"+f"(d[67]),"+f"(d[68]),"+f"(d[69]),"+f"(d[70]),"+f"(d[71]),"+f"(d[72]),"+f"(d[73]),"+f"(d[74]),"+f"(d[75]),"+f"(d[76]),"+f"(d[77]),"+f"(d[78]),"+f"(d[79]),"+f"(d[80]),"+f"(d[81]),"+f"(d[82]),"+f"(d[83]),"+f"(d[84]),"+f"(d[85]),"+f"(d[86]),"+f"(d[87])
    : "r"(a0), "r"(a1), "r"(a2), "r"(a3), "r"(blo), "r"(bhi), "n"(TB), "r"(sd)); }
};
template<> struct WG<192> { template<int TA, int TB> static __device__ __forceinline__ void ss(float* d, uint32_t alo, uint32_t ahi, uint32_t blo, uint32_t bhi, int sd) {
  asm volatile("{ .reg .pred p; .reg .b64 da, db; mov.b64 da, {%96,%97}; mov.b64 db, {%98,%99}; setp.ne.b32 p, %100, 0;\n"
    "wgmma.mma_async.sync.aligned.m64n192k16.f32.bf16.bf16 {%0,%1,%2,%3,%4,%5,%6,%7,%8,%9,%10,%11,%12,%13,%14,%15,%16,%17,%18,%19,%20,%21,%22,%23,%24,%25,%26,%27,%28,%29,%30,%31,%32,%33,%34,%35,%36,%37,%38,%39,%40,%41,%42,%43,%44,%45,%46,%47,%48,%49,%50,%51,%52,%53,%54,%55,%56,%57,%58,%59,%60,%61,%62,%63,%64,%65,%66,%67,%68,%69,%70,%71,%72,%73,%74,%75,%76,%77,%78,%79,%80,%81,%82,%83,%84,%85,%86,%87,%88,%89,%90,%91,%92,%93,%94,%95}, da, db, p, 1, 1, %101, %102; }"
    : "+f"(d[0]),"+f"(d[1]),"+f"(d[2]),"+f"(d[3]),"+f"(d[4]),"+f"(d[5]),"+f"(d[6]),"+f"(d[7]),"+f"(d[8]),"+f"(d[9]),"+f"(d[10]),"+f"(d[11]),"+f"(d[12]),"+f"(d[13]),"+f"(d[14]),"+f"(d[15]),"+f"(d[16]),"+f"(d[17]),"+f"(d[18]),"+f"(d[19]),"+f"(d[20]),"+f"(d[21]),"+f"(d[22]),"+f"(d[23]),"+f"(d[24]),"+f"(d[25]),"+f"(d[26]),"+f"(d[27]),"+f"(d[28]),"+f"(d[29]),"+f"(d[30]),"+f"(d[31]),"+f"(d[32]),"+f"(d[33]),"+f"(d[34]),"+f"(d[35]),"+f"(d[36]),"+f"(d[37]),"+f"(d[38]),"+f"(d[39]),"+f"(d[40]),"+f"(d[41]),"+f"(d[42]),"+f"(d[43]),"+f"(d[44]),"+f"(d[45]),"+f"(d[46]),"+f"(d[47]),"+f"(d[48]),"+f"(d[49]),"+f"(d[50]),"+f"(d[51]),"+f"(d[52]),"+f"(d[53]),"+f"(d[54]),"+f"(d[55]),"+f"(d[56]),"+f"(d[57]),"+f"(d[58]),"+f"(d[59]),"+f"(d[60]),"+f"(d[61]),"+f"(d[62]),"+f"(d[63]),"+f"(d[64]),"+f"(d[65]),"+f"(d[66]),"+f"(d[67]),"+f"(d[68]),"+f"(d[69]),"+f"(d[70]),"+f"(d[71]),"+f"(d[72]),"+f"(d[73]),"+f"(d[74]),"+f"(d[75]),"+f"(d[76]),"+f"(d[77]),"+f"(d[78]),"+f"(d[79]),"+f"(d[80]),"+f"(d[81]),"+f"(d[82]),"+f"(d[83]),"+f"(d[84]),"+f"(d[85]),"+f"(d[86]),"+f"(d[87]),"+f"(d[88]),"+f"(d[89]),"+f"(d[90]),"+f"(d[91]),"+f"(d[92]),"+f"(d[93]),"+f"(d[94]),"+f"(d[95])
    : "r"(alo), "r"(ahi), "r"(blo), "r"(bhi), "r"(sd), "n"(TA), "n"(TB)); }
  template<int TB> static __device__ __forceinline__ void rs(float* d, uint32_t a0, uint32_t a1, uint32_t a2, uint32_t a3, uint32_t blo, uint32_t bhi, int sd) {
  asm volatile("{ .reg .pred p; .reg .b64 db; mov.b64 db, {%100,%101}; setp.ne.b32 p, %103, 0;\n"
    "wgmma.mma_async.sync.aligned.m64n192k16.f32.bf16.bf16 {%0,%1,%2,%3,%4,%5,%6,%7,%8,%9,%10,%11,%12,%13,%14,%15,%16,%17,%18,%19,%20,%21,%22,%23,%24,%25,%26,%27,%28,%29,%30,%31,%32,%33,%34,%35,%36,%37,%38,%39,%40,%41,%42,%43,%44,%45,%46,%47,%48,%49,%50,%51,%52,%53,%54,%55,%56,%57,%58,%59,%60,%61,%62,%63,%64,%65,%66,%67,%68,%69,%70,%71,%72,%73,%74,%75,%76,%77,%78,%79,%80,%81,%82,%83,%84,%85,%86,%87,%88,%89,%90,%91,%92,%93,%94,%95}, {%96,%97,%98,%99}, db, p, 1, 1, %102; }"
    : "+f"(d[0]),"+f"(d[1]),"+f"(d[2]),"+f"(d[3]),"+f"(d[4]),"+f"(d[5]),"+f"(d[6]),"+f"(d[7]),"+f"(d[8]),"+f"(d[9]),"+f"(d[10]),"+f"(d[11]),"+f"(d[12]),"+f"(d[13]),"+f"(d[14]),"+f"(d[15]),"+f"(d[16]),"+f"(d[17]),"+f"(d[18]),"+f"(d[19]),"+f"(d[20]),"+f"(d[21]),"+f"(d[22]),"+f"(d[23]),"+f"(d[24]),"+f"(d[25]),"+f"(d[26]),"+f"(d[27]),"+f"(d[28]),"+f"(d[29]),"+f"(d[30]),"+f"(d[31]),"+f"(d[32]),"+f"(d[33]),"+f"(d[34]),"+f"(d[35]),"+f"(d[36]),"+f"(d[37]),"+f"(d[38]),"+f"(d[39]),"+f"(d[40]),"+f"(d[41]),"+f"(d[42]),"+f"(d[43]),"+f"(d[44]),"+f"(d[45]),"+f"(d[46]),"+f"(d[47]),"+f"(d[48]),"+f"(d[49]),"+f"(d[50]),"+f"(d[51]),"+f"(d[52]),"+f"(d[53]),"+f"(d[54]),"+f"(d[55]),"+f"(d[56]),"+f"(d[57]),"+f"(d[58]),"+f"(d[59]),"+f"(d[60]),"+f"(d[61]),"+f"(d[62]),"+f"(d[63]),"+f"(d[64]),"+f"(d[65]),"+f"(d[66]),"+f"(d[67]),"+f"(d[68]),"+f"(d[69]),"+f"(d[70]),"+f"(d[71]),"+f"(d[72]),"+f"(d[73]),"+f"(d[74]),"+f"(d[75]),"+f"(d[76]),"+f"(d[77]),"+f"(d[78]),"+f"(d[79]),"+f"(d[80]),"+f"(d[81]),"+f"(d[82]),"+f"(d[83]),"+f"(d[84]),"+f"(d[85]),"+f"(d[86]),"+f"(d[87]),"+f"(d[88]),"+f"(d[89]),"+f"(d[90]),"+f"(d[91]),"+f"(d[92]),"+f"(d[93]),"+f"(d[94]),"+f"(d[95])
    : "r"(a0), "r"(a1), "r"(a2), "r"(a3), "r"(blo), "r"(bhi), "n"(TB), "r"(sd)); }
};
template<> struct WG<208> { template<int TA, int TB> static __device__ __forceinline__ void ss(float* d, uint32_t alo, uint32_t ahi, uint32_t blo, uint32_t bhi, int sd) {
  asm volatile("{ .reg .pred p; .reg .b64 da, db; mov.b64 da, {%104,%105}; mov.b64 db, {%106,%107}; setp.ne.b32 p, %108, 0;\n"
    "wgmma.mma_async.sync.aligned.m64n208k16.f32.bf16.bf16 {%0,%1,%2,%3,%4,%5,%6,%7,%8,%9,%10,%11,%12,%13,%14,%15,%16,%17,%18,%19,%20,%21,%22,%23,%24,%25,%26,%27,%28,%29,%30,%31,%32,%33,%34,%35,%36,%37,%38,%39,%40,%41,%42,%43,%44,%45,%46,%47,%48,%49,%50,%51,%52,%53,%54,%55,%56,%57,%58,%59,%60,%61,%62,%63,%64,%65,%66,%67,%68,%69,%70,%71,%72,%73,%74,%75,%76,%77,%78,%79,%80,%81,%82,%83,%84,%85,%86,%87,%88,%89,%90,%91,%92,%93,%94,%95,%96,%97,%98,%99,%100,%101,%102,%103}, da, db, p, 1, 1, %109, %110; }"
    : "+f"(d[0]),"+f"(d[1]),"+f"(d[2]),"+f"(d[3]),"+f"(d[4]),"+f"(d[5]),"+f"(d[6]),"+f"(d[7]),"+f"(d[8]),"+f"(d[9]),"+f"(d[10]),"+f"(d[11]),"+f"(d[12]),"+f"(d[13]),"+f"(d[14]),"+f"(d[15]),"+f"(d[16]),"+f"(d[17]),"+f"(d[18]),"+f"(d[19]),"+f"(d[20]),"+f"(d[21]),"+f"(d[22]),"+f"(d[23]),"+f"(d[24]),"+f"(d[25]),"+f"(d[26]),"+f"(d[27]),"+f"(d[28]),"+f"(d[29]),"+f"(d[30]),"+f"(d[31]),"+f"(d[32]),"+f"(d[33]),"+f"(d[34]),"+f"(d[35]),"+f"(d[36]),"+f"(d[37]),"+f"(d[38]),"+f"(d[39]),"+f"(d[40]),"+f"(d[41]),"+f"(d[42]),"+f"(d[43]),"+f"(d[44]),"+f"(d[45]),"+f"(d[46]),"+f"(d[47]),"+f"(d[48]),"+f"(d[49]),"+f"(d[50]),"+f"(d[51]),"+f"(d[52]),"+f"(d[53]),"+f"(d[54]),"+f"(d[55]),"+f"(d[56]),"+f"(d[57]),"+f"(d[58]),"+f"(d[59]),"+f"(d[60]),"+f"(d[61]),"+f"(d[62]),"+f"(d[63]),"+f"(d[64]),"+f"(d[65]),"+f"(d[66]),"+f"(d[67]),"+f"(d[68]),"+f"(d[69]),"+f"(d[70]),"+f"(d[71]),"+f"(d[72]),"+f"(d[73]),"+f"(d[74]),"+f"(d[75]),"+f"(d[76]),"+f"(d[77]),"+f"(d[78]),"+f"(d[79]),"+f"(d[80]),"+f"(d[81]),"+f"(d[82]),"+f"(d[83]),"+f"(d[84]),"+f"(d[85]),"+f"(d[86]),"+f"(d[87]),"+f"(d[88]),"+f"(d[89]),"+f"(d[90]),"+f"(d[91]),"+f"(d[92]),"+f"(d[93]),"+f"(d[94]),"+f"(d[95]),"+f"(d[96]),"+f"(d[97]),"+f"(d[98]),"+f"(d[99]),"+f"(d[100]),"+f"(d[101]),"+f"(d[102]),"+f"(d[103])
    : "r"(alo), "r"(ahi), "r"(blo), "r"(bhi), "r"(sd), "n"(TA), "n"(TB)); }
  template<int TB> static __device__ __forceinline__ void rs(float* d, uint32_t a0, uint32_t a1, uint32_t a2, uint32_t a3, uint32_t blo, uint32_t bhi, int sd) {
  asm volatile("{ .reg .pred p; .reg .b64 db; mov.b64 db, {%108,%109}; setp.ne.b32 p, %111, 0;\n"
    "wgmma.mma_async.sync.aligned.m64n208k16.f32.bf16.bf16 {%0,%1,%2,%3,%4,%5,%6,%7,%8,%9,%10,%11,%12,%13,%14,%15,%16,%17,%18,%19,%20,%21,%22,%23,%24,%25,%26,%27,%28,%29,%30,%31,%32,%33,%34,%35,%36,%37,%38,%39,%40,%41,%42,%43,%44,%45,%46,%47,%48,%49,%50,%51,%52,%53,%54,%55,%56,%57,%58,%59,%60,%61,%62,%63,%64,%65,%66,%67,%68,%69,%70,%71,%72,%73,%74,%75,%76,%77,%78,%79,%80,%81,%82,%83,%84,%85,%86,%87,%88,%89,%90,%91,%92,%93,%94,%95,%96,%97,%98,%99,%100,%101,%102,%103}, {%104,%105,%106,%107}, db, p, 1, 1, %110; }"
    : "+f"(d[0]),"+f"(d[1]),"+f"(d[2]),"+f"(d[3]),"+f"(d[4]),"+f"(d[5]),"+f"(d[6]),"+f"(d[7]),"+f"(d[8]),"+f"(d[9]),"+f"(d[10]),"+f"(d[11]),"+f"(d[12]),"+f"(d[13]),"+f"(d[14]),"+f"(d[15]),"+f"(d[16]),"+f"(d[17]),"+f"(d[18]),"+f"(d[19]),"+f"(d[20]),"+f"(d[21]),"+f"(d[22]),"+f"(d[23]),"+f"(d[24]),"+f"(d[25]),"+f"(d[26]),"+f"(d[27]),"+f"(d[28]),"+f"(d[29]),"+f"(d[30]),"+f"(d[31]),"+f"(d[32]),"+f"(d[33]),"+f"(d[34]),"+f"(d[35]),"+f"(d[36]),"+f"(d[37]),"+f"(d[38]),"+f"(d[39]),"+f"(d[40]),"+f"(d[41]),"+f"(d[42]),"+f"(d[43]),"+f"(d[44]),"+f"(d[45]),"+f"(d[46]),"+f"(d[47]),"+f"(d[48]),"+f"(d[49]),"+f"(d[50]),"+f"(d[51]),"+f"(d[52]),"+f"(d[53]),"+f"(d[54]),"+f"(d[55]),"+f"(d[56]),"+f"(d[57]),"+f"(d[58]),"+f"(d[59]),"+f"(d[60]),"+f"(d[61]),"+f"(d[62]),"+f"(d[63]),"+f"(d[64]),"+f"(d[65]),"+f"(d[66]),"+f"(d[67]),"+f"(d[68]),"+f"(d[69]),"+f"(d[70]),"+f"(d[71]),"+f"(d[72]),"+f"(d[73]),"+f"(d[74]),"+f"(d[75]),"+f"(d[76]),"+f"(d[77]),"+f"(d[78]),"+f"(d[79]),"+f"(d[80]),"+f"(d[81]),"+f"(d[82]),"+f"(d[83]),"+f"(d[84]),"+f"(d[85]),"+f"(d[86]),"+f"(d[87]),"+f"(d[88]),"+f"(d[89]),"+f"(d[90]),"+f"(d[91]),"+f"(d[92]),"+f"(d[93]),"+f"(d[94]),"+f"(d[95]),"+f"(d[96]),"+f"(d[97]),"+f"(d[98]),"+f"(d[99]),"+f"(d[100]),"+f"(d[101]),"+f"(d[102]),"+f"(d[103])
    : "r"(a0), "r"(a1), "r"(a2), "r"(a3), "r"(blo), "r"(bhi), "n"(TB), "r"(sd)); }
};
template<> struct WG<224> { template<int TA, int TB> static __device__ __forceinline__ void ss(float* d, uint32_t alo, uint32_t ahi, uint32_t blo, uint32_t bhi, int sd) {
  asm volatile("{ .reg .pred p; .reg .b64 da, db; mov.b64 da, {%112,%113}; mov.b64 db, {%114,%115}; setp.ne.b32 p, %116, 0;\n"
    "wgmma.mma_async.sync.aligned.m64n224k16.f32.bf16.bf16 {%0,%1,%2,%3,%4,%5,%6,%7,%8,%9,%10,%11,%12,%13,%14,%15,%16,%17,%18,%19,%20,%21,%22,%23,%24,%25,%26,%27,%28,%29,%30,%31,%32,%33,%34,%35,%36,%37,%38,%39,%40,%41,%42,%43,%44,%45,%46,%47,%48,%49,%50,%51,%52,%53,%54,%55,%56,%57,%58,%59,%60,%61,%62,%63,%64,%65,%66,%67,%68,%69,%70,%71,%72,%73,%74,%75,%76,%77,%78,%79,%80,%81,%82,%83,%84,%85,%86,%87,%88,%89,%90,%91,%92,%93,%94,%95,%96,%97,%98,%99,%100,%101,%102,%103,%104,%105,%106,%107,%108,%109,%110,%111}, da, db, p, 1, 1, %117, %118; }"
    : "+f"(d[0]),"+f"(d[1]),"+f"(d[2]),"+f"(d[3]),"+f"(d[4]),"+f"(d[5]),"+f"(d[6]),"+f"(d[7]),"+f"(d[8]),"+f"(d[9]),"+f"(d[10]),"+f"(d[11]),"+f"(d[12]),"+f"(d[13]),"+f"(d[14]),"+f"(d[15]),"+f"(d[16]),"+f"(d[17]),"+f"(d[18]),"+f"(d[19]),"+f"(d[20]),"+f"(d[21]),"+f"(d[22]),"+f"(d[23]),"+f"(d[24]),"+f"(d[25]),"+f"(d[26]),"+f"(d[27]),"+f"(d[28]),"+f"(d[29]),"+f"(d[30]),"+f"(d[31]),"+f"(d[32]),"+f"(d[33]),"+f"(d[34]),"+f"(d[35]),"+f"(d[36]),"+f"(d[37]),"+f"(d[38]),"+f"(d[39]),"+f"(d[40]),"+f"(d[41]),"+f"(d[42]),"+f"(d[43]),"+f"(d[44]),"+f"(d[45]),"+f"(d[46]),"+f"(d[47]),"+f"(d[48]),"+f"(d[49]),"+f"(d[50]),"+f"(d[51]),"+f"(d[52]),"+f"(d[53]),"+f"(d[54]),"+f"(d[55]),"+f"(d[56]),"+f"(d[57]),"+f"(d[58]),"+f"(d[59]),"+f"(d[60]),"+f"(d[61]),"+f"(d[62]),"+f"(d[63]),"+f"(d[64]),"+f"(d[65]),"+f"(d[66]),"+f"(d[67]),"+f"(d[68]),"+f"(d[69]),"+f"(d[70]),"+f"(d[71]),"+f"(d[72]),"+f"(d[73]),"+f"(d[74]),"+f"(d[75]),"+f"(d[76]),"+f"(d[77]),"+f"(d[78]),"+f"(d[79]),"+f"(d[80]),"+f"(d[81]),"+f"(d[82]),"+f"(d[83]),"+f"(d[84]),"+f"(d[85]),"+f"(d[86]),"+f"(d[87]),"+f"(d[88]),"+f"(d[89]),"+f"(d[90]),"+f"(d[91]),"+f"(d[92]),"+f"(d[93]),"+f"(d[94]),"+f"(d[95]),"+f"(d[96]),"+f"(d[97]),"+f"(d[98]),"+f"(d[99]),"+f"(d[100]),"+f"(d[101]),"+f"(d[102]),"+f"(d[103]),"+f"(d[104]),"+f"(d[105]),"+f"(d[106]),"+f"(d[107]),"+f"(d[108]),"+f"(d[109]),"+f"(d[110]),"+f"(d[111])
    : "r"(alo), "r"(ahi), "r"(blo), "r"(bhi), "r"(sd), "n"(TA), "n"(TB)); }
  template<int TB> static __device__ __forceinline__ void rs(float* d, uint32_t a0, uint32_t a1, uint32_t a2, uint32_t a3, uint32_t blo, uint32_t bhi, int sd) {
  asm volatile("{ .reg .pred p; .reg .b64 db; mov.b64 db, {%116,%117}; setp.ne.b32 p, %119, 0;\n"
    "wgmma.mma_async.sync.aligned.m64n224k16.f32.bf16.bf16 {%0,%1,%2,%3,%4,%5,%6,%7,%8,%9,%10,%11,%12,%13,%14,%15,%16,%17,%18,%19,%20,%21,%22,%23,%24,%25,%26,%27,%28,%29,%30,%31,%32,%33,%34,%35,%36,%37,%38,%39,%40,%41,%42,%43,%44,%45,%46,%47,%48,%49,%50,%51,%52,%53,%54,%55,%56,%57,%58,%59,%60,%61,%62,%63,%64,%65,%66,%67,%68,%69,%70,%71,%72,%73,%74,%75,%76,%77,%78,%79,%80,%81,%82,%83,%84,%85,%86,%87,%88,%89,%90,%91,%92,%93,%94,%95,%96,%97,%98,%99,%100,%101,%102,%103,%104,%105,%106,%107,%108,%109,%110,%111}, {%112,%113,%114,%115}, db, p, 1, 1, %118; }"
    : "+f"(d[0]),"+f"(d[1]),"+f"(d[2]),"+f"(d[3]),"+f"(d[4]),"+f"(d[5]),"+f"(d[6]),"+f"(d[7]),"+f"(d[8]),"+f"(d[9]),"+f"(d[10]),"+f"(d[11]),"+f"(d[12]),"+f"(d[13]),"+f"(d[14]),"+f"(d[15]),"+f"(d[16]),"+f"(d[17]),"+f"(d[18]),"+f"(d[19]),"+f"(d[20]),"+f"(d[21]),"+f"(d[22]),"+f"(d[23]),"+f"(d[24]),"+f"(d[25]),"+f"(d[26]),"+f"(d[27]),"+f"(d[28]),"+f"(d[29]),"+f"(d[30]),"+f"(d[31]),"+f"(d[32]),"+f"(d[33]),"+f"(d[34]),"+f"(d[35]),"+f"(d[36]),"+f"(d[37]),"+f"(d[38]),"+f"(d[39]),"+f"(d[40]),"+f"(d[41]),"+f"(d[42]),"+f"(d[43]),"+f"(d[44]),"+f"(d[45]),"+f"(d[46]),"+f"(d[47]),"+f"(d[48]),"+f"(d[49]),"+f"(d[50]),"+f"(d[51]),"+f"(d[52]),"+f"(d[53]),"+f"(d[54]),"+f"(d[55]),"+f"(d[56]),"+f"(d[57]),"+f"(d[58]),"+f"(d[59]),"+f"(d[60]),"+f"(d[61]),"+f"(d[62]),"+f"(d[63]),"+f"(d[64]),"+f"(d[65]),"+f"(d[66]),"+f"(d[67]),"+f"(d[68]),"+f"(d[69]),"+f"(d[70]),"+f"(d[71]),"+f"(d[72]),"+f"(d[73]),"+f"(d[74]),"+f"(d[75]),"+f"(d[76]),"+f"(d[77]),"+f"(d[78]),"+f"(d[79]),"+f"(d[80]),"+f"(d[81]),"+f"(d[82]),"+f"(d[83]),"+f"(d[84]),"+f"(d[85]),"+f"(d[86]),"+f"(d[87]),"+f"(d[88]),"+f"(d[89]),"+f"(d[90]),"+f"(d[91]),"+f"(d[92]),"+f"(d[93]),"+f"(d[94]),"+f"(d[95]),"+f"(d[96]),"+f"(d[97]),"+f"(d[98]),"+f"(d[99]),"+f"(d[100]),"+f"(d[101]),"+f"(d[102]),"+f"(d[103]),"+f"(d[104]),"+f"(d[105]),"+f"(d[106]),"+f"(d[107]),"+f"(d[108]),"+f"(d[109]),"+f"(d[110]),"+f"(d[111])
    : "r"(a0), "r"(a1), "r"(a2), "r"(a3), "r"(blo), "r"(bhi), "n"(TB), "r"(sd)); }
};
template<> struct WG<240> { template<int TA, int TB> static __device__ __forceinline__ void ss(float* d, uint32_t alo, uint32_t ahi, uint32_t blo, uint32_t bhi, int sd) {
  asm volatile("{ .reg .pred p; .reg .b64 da, db; mov.b64 da, {%120,%121}; mov.b64 db, {%122,%123}; setp.ne.b32 p, %124, 0;\n"
    "wgmma.mma_async.sync.aligned.m64n240k16.f32.bf16.bf16 {%0,%1,%2,%3,%4,%5,%6,%7,%8,%9,%10,%11,%12,%13,%14,%15,%16,%17,%18,%19,%20,%21,%22,%23,%24,%25,%26,%27,%28,%29,%30,%31,%32,%33,%34,%35,%36,%37,%38,%39,%40,%41,%42,%43,%44,%45,%46,%47,%48,%49,%50,%51,%52,%53,%54,%55,%56,%57,%58,%59,%60,%61,%62,%63,%64,%65,%66,%67,%68,%69,%70,%71,%72,%73,%74,%75,%76,%77,%78,%79,%80,%81,%82,%83,%84,%85,%86,%87,%88,%89,%90,%91,%92,%93,%94,%95,%96,%97,%98,%99,%100,%101,%102,%103,%104,%105,%106,%107,%108,%109,%110,%111,%112,%113,%114,%115,%116,%117,%118,%119}, da, db, p, 1, 1, %125, %126; }"
    : "+f"(d[0]),"+f"(d[1]),"+f"(d[2]),"+f"(d[3]),"+f"(d[4]),"+f"(d[5]),"+f"(d[6]),"+f"(d[7]),"+f"(d[8]),"+f"(d[9]),"+f"(d[10]),"+f"(d[11]),"+f"(d[12]),"+f"(d[13]),"+f"(d[14]),"+f"(d[15]),"+f"(d[16]),"+f"(d[17]),"+f"(d[18]),"+f"(d[19]),"+f"(d[20]),"+f"(d[21]),"+f"(d[22]),"+f"(d[23]),"+f"(d[24]),"+f"(d[25]),"+f"(d[26]),"+f"(d[27]),"+f"(d[28]),"+f"(d[29]),"+f"(d[30]),"+f"(d[31]),"+f"(d[32]),"+f"(d[33]),"+f"(d[34]),"+f"(d[35]),"+f"(d[36]),"+f"(d[37]),"+f"(d[38]),"+f"(d[39]),"+f"(d[40]),"+f"(d[41]),"+f"(d[42]),"+f"(d[43]),"+f"(d[44]),"+f"(d[45]),"+f"(d[46]),"+f"(d[47]),"+f"(d[48]),"+f"(d[49]),"+f"(d[50]),"+f"(d[51]),"+f"(d[52]),"+f"(d[53]),"+f"(d[54]),"+f"(d[55]),"+f"(d[56]),"+f"(d[57]),"+f"(d[58]),"+f"(d[59]),"+f"(d[60]),"+f"(d[61]),"+f"(d[62]),"+f"(d[63]),"+f"(d[64]),"+f"(d[65]),"+f"(d[66]),"+f"(d[67]),"+f"(d[68]),"+f"(d[69]),"+f"(d[70]),"+f"(d[71]),"+f"(d[72]),"+f"(d[73]),"+f"(d[74]),"+f"(d[75]),"+f"(d[76]),"+f"(d[77]),"+f"(d[78]),"+f"(d[79]),"+f"(d[80]),"+f"(d[81]),"+f"(d[82]),"+f"(d[83]),"+f"(d[84]),"+f"(d[85]),"+f"(d[86]),"+f"(d[87]),"+f"(d[88]),"+f"(d[89]),"+f"(d[90]),"+f"(d[91]),"+f"(d[92]),"+f"(d[93]),"+f"(d[94]),"+f"(d[95]),"+f"(d[96]),"+f"(d[97]),"+f"(d[98]),"+f"(d[99]),"+f"(d[100]),"+f"(d[101]),"+f"(d[102]),"+f"(d[103]),"+f"(d[104]),"+f"(d[105]),"+f"(d[106]),"+f"(d[107]),"+f"(d[108]),"+f"(d[109]),"+f"(d[110]),"+f"(d[111]),"+f"(d[112]),"+f"(d[113]),"+f"(d[114]),"+f"(d[115]),"+f"(d[116]),"+f"(d[117]),"+f"(d[118]),"+f"(d[119])
    : "r"(alo), "r"(ahi), "r"(blo), "r"(bhi), "r"(sd), "n"(TA), "n"(TB)); }
  template<int TB> static __device__ __forceinline__ void rs(float* d, uint32_t a0, uint32_t a1, uint32_t a2, uint32_t a3, uint32_t blo, uint32_t bhi, int sd) {
  asm volatile("{ .reg .pred p; .reg .b64 db; mov.b64 db, {%124,%125}; setp.ne.b32 p, %127, 0;\n"
    "wgmma.mma_async.sync.aligned.m64n240k16.f32.bf16.bf16 {%0,%1,%2,%3,%4,%5,%6,%7,%8,%9,%10,%11,%12,%13,%14,%15,%16,%17,%18,%19,%20,%21,%22,%23,%24,%25,%26,%27,%28,%29,%30,%31,%32,%33,%34,%35,%36,%37,%38,%39,%40,%41,%42,%43,%44,%45,%46,%47,%48,%49,%50,%51,%52,%53,%54,%55,%56,%57,%58,%59,%60,%61,%62,%63,%64,%65,%66,%67,%68,%69,%70,%71,%72,%73,%74,%75,%76,%77,%78,%79,%80,%81,%82,%83,%84,%85,%86,%87,%88,%89,%90,%91,%92,%93,%94,%95,%96,%97,%98,%99,%100,%101,%102,%103,%104,%105,%106,%107,%108,%109,%110,%111,%112,%113,%114,%115,%116,%117,%118,%119}, {%120,%121,%122,%123}, db, p, 1, 1, %126; }"
    : "+f"(d[0]),"+f"(d[1]),"+f"(d[2]),"+f"(d[3]),"+f"(d[4]),"+f"(d[5]),"+f"(d[6]),"+f"(d[7]),"+f"(d[8]),"+f"(d[9]),"+f"(d[10]),"+f"(d[11]),"+f"(d[12]),"+f"(d[13]),"+f"(d[14]),"+f"(d[15]),"+f"(d[16]),"+f"(d[17]),"+f"(d[18]),"+f"(d[19]),"+f"(d[20]),"+f"(d[21]),"+f"(d[22]),"+f"(d[23]),"+f"(d[24]),"+f"(d[25]),"+f"(d[26]),"+f"(d[27]),"+f"(d[28]),"+f"(d[29]),"+f"(d[30]),"+f"(d[31]),"+f"(d[32]),"+f"(d[33]),"+f"(d[34]),"+f"(d[35]),"+f"(d[36]),"+f"(d[37]),"+f"(d[38]),"+f"(d[39]),"+f"(d[40]),"+f"(d[41]),"+f"(d[42]),"+f"(d[43]),"+f"(d[44]),"+f"(d[45]),"+f"(d[46]),"+f"(d[47]),"+f"(d[48]),"+f"(d[49]),"+f"(d[50]),"+f"(d[51]),"+f"(d[52]),"+f"(d[53]),"+f"(d[54]),"+f"(d[55]),"+f"(d[56]),"+f"(d[57]),"+f"(d[58]),"+f"(d[59]),"+f"(d[60]),"+f"(d[61]),"+f"(d[62]),"+f"(d[63]),"+f"(d[64]),"+f"(d[65]),"+f"(d[66]),"+f"(d[67]),"+f"(d[68]),"+f"(d[69]),"+f"(d[70]),"+f"(d[71]),"+f"(d[72]),"+f"(d[73]),"+f"(d[74]),"+f"(d[75]),"+f"(d[76]),"+f"(d[77]),"+f"(d[78]),"+f"(d[79]),"+f"(d[80]),"+f"(d[81]),"+f"(d[82]),"+f"(d[83]),"+f"(d[84]),"+f"(d[85]),"+f"(d[86]),"+f"(d[87]),"+f"(d[88]),"+f"(d[89]),"+f"(d[90]),"+f"(d[91]),"+f"(d[92]),"+f"(d[93]),"+f"(d[94]),"+f"(d[95]),"+f"(d[96]),"+f"(d[97]),"+f"(d[98]),"+f"(d[99]),"+f"(d[100]),"+f"(d[101]),"+f"(d[102]),"+f"(d[103]),"+f"(d[104]),"+f"(d[105]),"+f"(d[106]),"+f"(d[107]),"+f"(d[108]),"+f"(d[109]),"+f"(d[110]),"+f"(d[111]),"+f"(d[112]),"+f"(d[113]),"+f"(d[114]),"+f"(d[115]),"+f"(d[116]),"+f"(d[117]),"+f"(d[118]),"+f"(d[119])
    : "r"(a0), "r"(a1), "r"(a2), "r"(a3), "r"(blo), "r"(bhi), "n"(TB), "r"(sd)); }
};
template<> struct WG<256> { template<int TA, int TB> static __device__ __forceinline__ void ss(float* d, uint32_t alo, uint32_t ahi, uint32_t blo, uint32_t bhi, int sd) {
  asm volatile("{ .reg .pred p; .reg .b64 da, db; mov.b64 da, {%128,%129}; mov.b64 db, {%130,%131}; setp.ne.b32 p, %132, 0;\n"
    "wgmma.mma_async.sync.aligned.m64n256k16.f32.bf16.bf16 {%0,%1,%2,%3,%4,%5,%6,%7,%8,%9,%10,%11,%12,%13,%14,%15,%16,%17,%18,%19,%20,%21,%22,%23,%24,%25,%26,%27,%28,%29,%30,%31,%32,%33,%34,%35,%36,%37,%38,%39,%40,%41,%42,%43,%44,%45,%46,%47,%48,%49,%50,%51,%52,%53,%54,%55,%56,%57,%58,%59,%60,%61,%62,%63,%64,%65,%66,%67,%68,%69,%70,%71,%72,%73,%74,%75,%76,%77,%78,%79,%80,%81,%82,%83,%84,%85,%86,%87,%88,%89,%90,%91,%92,%93,%94,%95,%96,%97,%98,%99,%100,%101,%102,%103,%104,%105,%106,%107,%108,%109,%110,%111,%112,%113,%114,%115,%116,%117,%118,%119,%120,%121,%122,%123,%124,%125,%126,%127}, da, db, p, 1, 1, %133, %134; }"
    : "+f"(d[0]),"+f"(d[1]),"+f"(d[2]),"+f"(d[3]),"+f"(d[4]),"+f"(d[5]),"+f"(d[6]),"+f"(d[7]),"+f"(d[8]),"+f"(d[9]),"+f"(d[10]),"+f"(d[11]),"+f"(d[12]),"+f"(d[13]),"+f"(d[14]),"+f"(d[15]),"+f"(d[16]),"+f"(d[17]),"+f"(d[18]),"+f"(d[19]),"+f"(d[20]),"+f"(d[21]),"+f"(d[22]),"+f"(d[23]),"+f"(d[24]),"+f"(d[25]),"+f"(d[26]),"+f"(d[27]),"+f"(d[28]),"+f"(d[29]),"+f"(d[30]),"+f"(d[31]),"+f"(d[32]),"+f"(d[33]),"+f"(d[34]),"+f"(d[35]),"+f"(d[36]),"+f"(d[37]),"+f"(d[38]),"+f"(d[39]),"+f"(d[40]),"+f"(d[41]),"+f"(d[42]),"+f"(d[43]),"+f"(d[44]),"+f"(d[45]),"+f"(d[46]),"+f"(d[47]),"+f"(d[48]),"+f"(d[49]),"+f"(d[50]),"+f"(d[51]),"+f"(d[52]),"+f"(d[53]),"+f"(d[54]),"+f"(d[55]),"+f"(d[56]),"+f"(d[57]),"+f"(d[58]),"+f"(d[59]),"+f"(d[60]),"+f"(d[61]),"+f"(d[62]),"+f"(d[63]),"+f"(d[64]),"+f"(d[65]),"+f"(d[66]),"+f"(d[67]),"+f"(d[68]),"+f"(d[69]),"+f"(d[70]),"+f"(d[71]),"+f"(d[72]),"+f"(d[73]),"+f"(d[74]),"+f"(d[75]),"+f"(d[76]),"+f"(d[77]),"+f"(d[78]),"+f"(d[79]),"+f"(d[80]),"+f"(d[81]),"+f"(d[82]),"+f"(d[83]),"+f"(d[84]),"+f"(d[85]),"+f"(d[86]),"+f"(d[87]),"+f"(d[88]),"+f"(d[89]),"+f"(d[90]),"+f"(d[91]),"+f"(d[92]),"+f"(d[93]),"+f"(d[94]),"+f"(d[95]),"+f"(d[96]),"+f"(d[97]),"+f"(d[98]),"+f"(d[99]),"+f"(d[100]),"+f"(d[101]),"+f"(d[102]),"+f"(d[103]),"+f"(d[104]),"+f"(d[105]),"+f"(d[106]),"+f"(d[107]),"+f"(d[108]),"+f"(d[109]),"+f"(d[110]),"+f"(d[111]),"+f"(d[112]),"+f"(d[113]),"+f"(d[114]),"+f"(d[115]),"+f"(d[116]),"+f"(d[117]),"+f"(d[118]),"+f"(d[119]),"+f"(d[120]),"+f"(d[121]),"+f"(d[122]),"+f"(d[123]),"+f"(d[124]),"+f"(d[125]),"+f"(d[126]),"+f"(d[127])
    : "r"(alo), "r"(ahi), "r"(blo), "r"(bhi), "r"(sd), "n"(TA), "n"(TB)); }
  template<int TB> static __device__ __forceinline__ void rs(float* d, uint32_t a0, uint32_t a1, uint32_t a2, uint32_t a3, uint32_t blo, uint32_t bhi, int sd) {
  asm volatile("{ .reg .pred p; .reg .b64 db; mov.b64 db, {%132,%133}; setp.ne.b32 p, %135, 0;\n"
    "wgmma.mma_async.sync.aligned.m64n256k16.f32.bf16.bf16 {%0,%1,%2,%3,%4,%5,%6,%7,%8,%9,%10,%11,%12,%13,%14,%15,%16,%17,%18,%19,%20,%21,%22,%23,%24,%25,%26,%27,%28,%29,%30,%31,%32,%33,%34,%35,%36,%37,%38,%39,%40,%41,%42,%43,%44,%45,%46,%47,%48,%49,%50,%51,%52,%53,%54,%55,%56,%57,%58,%59,%60,%61,%62,%63,%64,%65,%66,%67,%68,%69,%70,%71,%72,%73,%74,%75,%76,%77,%78,%79,%80,%81,%82,%83,%84,%85,%86,%87,%88,%89,%90,%91,%92,%93,%94,%95,%96,%97,%98,%99,%100,%101,%102,%103,%104,%105,%106,%107,%108,%109,%110,%111,%112,%113,%114,%115,%116,%117,%118,%119,%120,%121,%122,%123,%124,%125,%126,%127}, {%128,%129,%130,%131}, db, p, 1, 1, %134; }"
    : "+f"(d[0]),"+f"(d[1]),"+f"(d[2]),"+f"(d[3]),"+f"(d[4]),"+f"(d[5]),"+f"(d[6]),"+f"(d[7]),"+f"(d[8]),"+f"(d[9]),"+f"(d[10]),"+f"(d[11]),"+f"(d[12]),"+f"(d[13]),"+f"(d[14]),"+f"(d[15]),"+f"(d[16]),"+f"(d[17]),"+f"(d[18]),"+f"(d[19]),"+f"(d[20]),"+f"(d[21]),"+f"(d[22]),"+f"(d[23]),"+f"(d[24]),"+f"(d[25]),"+f"(d[26]),"+f"(d[27]),"+f"(d[28]),"+f"(d[29]),"+f"(d[30]),"+f"(d[31]),"+f"(d[32]),"+f"(d[33]),"+f"(d[34]),"+f"(d[35]),"+f"(d[36]),"+f"(d[37]),"+f"(d[38]),"+f"(d[39]),"+f"(d[40]),"+f"(d[41]),"+f"(d[42]),"+f"(d[43]),"+f"(d[44]),"+f"(d[45]),"+f"(d[46]),"+f"(d[47]),"+f"(d[48]),"+f"(d[49]),"+f"(d[50]),"+f"(d[51]),"+f"(d[52]),"+f"(d[53]),"+f"(d[54]),"+f"(d[55]),"+f"(d[56]),"+f"(d[57]),"+f"(d[58]),"+f"(d[59]),"+f"(d[60]),"+f"(d[61]),"+f"(d[62]),"+f"(d[63]),"+f"(d[64]),"+f"(d[65]),"+f"(d[66]),"+f"(d[67]),"+f"(d[68]),"+f"(d[69]),"+f"(d[70]),"+f"(d[71]),"+f"(d[72]),"+f"(d[73]),"+f"(d[74]),"+f"(d[75]),"+f"(d[76]),"+f"(d[77]),"+f"(d[78]),"+f"(d[79]),"+f"(d[80]),"+f"(d[81]),"+f"(d[82]),"+f"(d[83]),"+f"(d[84]),"+f"(d[85]),"+f"(d[86]),"+f"(d[87]),"+f"(d[88]),"+f"(d[89]),"+f"(d[90]),"+f"(d[91]),"+f"(d[92]),"+f"(d[93]),"+f"(d[94]),"+f"(d[95]),"+f"(d[96]),"+f"(d[97]),"+f"(d[98]),"+f"(d[99]),"+f"(d[100]),"+f"(d[101]),"+f"(d[102]),"+f"(d[103]),"+f"(d[104]),"+f"(d[105]),"+f"(d[106]),"+f"(d[107]),"+f"(d[108]),"+f"(d[109]),"+f"(d[110]),"+f"(d[111]),"+f"(d[112]),"+f"(d[113]),"+f"(d[114]),"+f"(d[115]),"+f"(d[116]),"+f"(d[117]),"+f"(d[118]),"+f"(d[119]),"+f"(d[120]),"+f"(d[121]),"+f"(d[122]),"+f"(d[123]),"+f"(d[124]),"+f"(d[125]),"+f"(d[126]),"+f"(d[127])
    : "r"(a0), "r"(a1), "r"(a2), "r"(a3), "r"(blo), "r"(bhi), "n"(TB), "r"(sd)); }
};

template<int T> struct ConvR {
    static __device__ __forceinline__ void run(float* acc, const uint32_t* a, uint32_t db) {
        WG<256 - 16 * T>::template rs<0>(acc, a[4 * T], a[4 * T + 1], a[4 * T + 2], a[4 * T + 3], db + T * 16, dhi(128, 0), T != 0);
        ConvR<T + 1>::run(acc, a, db);
    }
};
template<> struct ConvR<16> { static __device__ __forceinline__ void run(float*, const uint32_t*, uint32_t) {} };

template<int P> __device__ __forceinline__ void hh_store(const uint32_t* hq, char* dst) { const uint32_t* o = hq + 4 * P; stg_b128(dst + (P >> 2) * 16384 + ((P >> 1) & 1) * 512 + (P & 1) * 1024, o[0], o[1], o[2], o[3]); }
template<int P, bool ST = true> __device__ __forceinline__ void ffn_epi(const float* g, const float* u, float rq0, float rq1, uint32_t* hq, char* dst, uint32_t tag) {
    const float rq = (P & 1) ? rq1 : rq0;
    uint32_t* o = hq + 4 * P;
    #pragma unroll
    for (int b = 0; b < 4; b++) { const int i = 16 * (P >> 1) + 4 * b + 2 * (P & 1); o[b] = hmul2(pack2relu(g[i], g[i + 1]), pack2(u[i] * rq, u[i + 1] * rq)); }
    o[2 * (P & 1) + ((P >> 1) & 1)] = tagbit(o[2 * (P & 1) + ((P >> 1) & 1)], tag);
    if (ST) hh_store<P>(hq, dst); else asm volatile("" : "+r"(o[0]), "+r"(o[1]), "+r"(o[2]), "+r"(o[3]));
}
__device__ __forceinline__ uint32_t tagged(float x, uint32_t tag) { return (__float_as_uint(x) & ~7u) | (tag & 7u); }
__device__ __forceinline__ uint32_t split2(float x) { const float h = bfround(x); return pack2(h, x - h); }
__device__ __forceinline__ void yield() { asm volatile("pmevent 1;" ::: "memory"); }
__device__ __forceinline__ void vfma(float& d, float a, float b) { asm volatile("fma.rn.f32 %0, %1, %2, %0;" : "+f"(d) : "f"(a), "f"(b)); }
__device__ __forceinline__ void vadd(float& d, float a) { asm volatile("add.f32 %0, %0, %1;" : "+f"(d) : "f"(a)); }
template<int I, int N, typename F> __device__ __forceinline__ void static_for(F&& f) {
    if constexpr (I < N) { f(std::integral_constant<int, I>{}); static_for<I + 1, N>(f); }
}

__device__ __forceinline__ int mod_col(int G) {
    const int s4 = (G >> 1) & 3;
    return G < 32 ? (s4 + (s4 == 3)) * 640 + (G >> 3) * 128 + (G & 1) * 64 : G < 34 ? 3072 + (G & 1) * 64 : G < 44 ? 1920 + (G - 34) * 64 :
           G < 50 ? ((G - 44) >> 1) * 640 + 512 + (G & 1) * 64 : 3200 + (G - 50) * 64;
}
__device__ __forceinline__ uint32_t silu2(uint32_t w) {
    const float a0 = bflo(w), a1 = bfhi(w);
    return pack2(__fdividef(a0, 1.f + __expf(-a0)), __fdividef(a1, 1.f + __expf(-a1)));
}

struct Maps { CUtensorMap k, v, q, o1, w[4]  , wd, wn, wm, out; };
struct Ptrs { const char *k, *v, *ssm, *shift, *ssmD, *c, *Wg, *Wu, *Wd; char *scr;
    Sched s;
};

__global__ void __cluster_dims__(2, 1, 1) __launch_bounds__(384, 1)
fused_kernel(const __grid_constant__ Ptrs P, const __grid_constant__ Maps M) {
    extern __shared__ __align__(1024) char smraw[];
    GSTAMPIF(threadIdx.x == 0, 63);
    uint32_t clk0;
    asm volatile("mov.u32 %0, %%clock;" : "=r"(clk0));
    const uint32_t sb = smem_u32(smraw);
    const int tid = threadIdx.x, lane = tid & 31;
    uint32_t tpc;
    asm("mov.u32 %0, %%smid;" : "=r"(tpc));
    tpc >>= 1;
    const int b = 2 * (tpc >= 62 ? tpc - 62 : tpc + 4) + (blockIdx.x & 1);
    const int warp = __shfl_sync(~0u, tid >> 5, 0);
    #define BAR(i) (sb + BARS + 8 * (i))
    #define CNT(i) ((uint32_t*)paddv(P.scr, (i) * 128))
    uint32_t epoch = 0;
    if (tid < 256) {
        asm volatile("ld.relaxed.gpu.global.u32 %0, [%1];" : "=r"(epoch) : "l"(CNT(C_ZO)) : "memory");
        if (tid < NPF && b < 128) asm volatile("prefetch.global.L2 [%0];" :: "l"(padd((tid & 32) ? P.v : P.k, (b * 16 + (lane >> 1)) * 1280 + (lane & 1) * 128 + (tid >> 6) * 256)) : "memory");
    }
    const int rank = b & 1, cl = b >> 1, cu = cl - 36, cv = (cu * 37) >> 8;
    const int gpc = cl < 4 ? 0 : cl < 36 ? (cl - 4) & 7 : 1 + cu - 7 * cv, pj = cl < 4 ? 4 + cl : cl < 36 ? (cl - 4) >> 3 : 4 + cv;
    const int sg = (0x73125460 >> (4 * gpc)) & 7;
    const int cg = 2 * (sg >> 2) + rank, tb = 8 * (sg & 3) + pj, bc = 32 * cg + tb;
    const int js = (sg & 4) + (pj & 3), tile = 4 * (sg & 3) + 2 * (pj >> 2) + rank;
    const int kh = js >> 2, dq = js & 3;
    auto load_kv = [&](int r) {
        tma3d(sb + kv_at(r), &M.k, r * 128 + cg * 32, 247 - 8 * tb, 0, BAR(B_KV + r));
        tma3d(sb + kv_at(r) + 4608, &M.v, r * 128 + cg * 32, 248 - 8 * tb, 0, BAR(B_KV + r));
    };
    auto load_h = [&](int r) { bulk_g2s(sb + HS + 16 + r * XP, padd(P.ssm, (bc + 128 * r) * 4096), 4096, BAR(B_H + r)); };
    if (b < 128 && warp == 9) {
        if (elect()) {
            pf_map(&M.k); pf_map(&M.v);
            mbar_init(BAR(B_KV), 1);
            fence_async_smem();
            mbar_expect(BAR(B_KV), KVP + 5120 + 1280);
            bulk_g2s(sb + SHT, P.shift, 5120, BAR(B_KV));
            bulk_g2s(sb + DS, P.ssmD, 1280, BAR(B_KV));
            load_kv(0);
            #pragma unroll
            for (int i = 1; i < B_XF; i++) mbar_init(BAR(i), 1);
            fence_async_smem();
        }
        __syncwarp();
    }
    const int kind = (lane * 13) >> 7, pr = (lane >> 1) - 5 * kind;
    const uint32_t* cp = nullptr;
    if (b < 128 && warp == 8) {
        const uint32_t base = (C_KV + (bc >> 5)) | (C_Y + cg) << 8 | (C_Z + tile) << 16 | (C_HH - 256 + tile * 2 + kh) << 24;
        cp = CNT((lane & 1) * 32 + ((base >> (8 * kind)) & 255) + (pr << (kind == 2 ? 6 : 2)) + (lane >= 30) * 256);
        asm volatile("cp.async.cg.shared.global [%0], [%1], 16;" :: "r"(sb + PS + lane * 16), "l"(cp) : "memory");
        sts32(sb + PRE + lane * 4, 0);
    }
    if (b >= 128) {
        if (tid == 256) { _Pragma("unroll") for (int i = 0; i < 16; i++) mbar_init(BAR(i), i < 8 ? 1 : 4); fence_async_smem(); }
        __syncthreads();
        if (warp >= 8) {
            if (elect()) {
                pf_map(&M.wm);
                wait_clock(clk0, P.s.d_sp + (warp - 8) * P.s.g_sp);
                _Pragma("unroll 1") for (int i = 0; i < 15; i++) {
                    const int col = mod_col(4 * i + b - 128), s = (i & 1) * 4 + warp - 8;
                    mbar_wait(BAR(8 + s), ~(i >> 1) & 1);
                    mbar_expect(BAR(s), 20480);
                    tma2d(sb + s * 20480, &M.wm, col, (warp - 8) * 160, BAR(s));
                    if (i == 0) pause(4 * P.s.g_sp);
                }
            }
        } else {
            const int wg = warp >> 2;
            sts32(sb + 204800 + tid * 4, silu2(__ldg((const uint32_t*)P.c + tid)));
            if (tid < 64) sts32(sb + 205824 + tid * 4, silu2(__ldg((const uint32_t*)P.c + 256 + tid)));
            fence_async_smem();
            bar_sync(1, 256);
            epoch = (epoch >> 7) + 1;
            _Pragma("unroll 1") for (int i = wg; i < 15; i += 2) {
                float acc[8];
                char* mp = SC(mod, (mod_col(4 * i + b - 128) + (warp & 3) * 16 + (lane >> 2)) * 8);
                _Pragma("unroll 1") for (int j = 0; j < 4; j++) {
                    const int s = wg * 4 + j;
                    const uint32_t da = dlo(sb + s * 20480, 16), db = dlo(sb + 204800 + j * 320, 16);
                    mbar_wait(BAR(s), (i >> 1) & 1);
                    wg_fence();
                    #pragma unroll
                    for (int ks = 0; ks < 10; ks++) WG<8>::ss<1, 0>(acc + 4 * (ks & 1), da + ks * 128, dhi(1024, 1), db + ks * 2, dhi(128, 0), ks > 1 || j != 0);
                    wg_commit();
                    wg_wait<0>();
                    pin<8>(acc);
                    mbar_arrive_if(BAR(8 + s), lane == 0);
                }
                if ((lane & 3) == 0) { ll_write1(mp, acc[0] + acc[4], epoch); ll_write1(mp + 64, acc[2] + acc[6], epoch); }
                STAMPIF(warp == 4, 110 + (i >> 1));
                STAMPIF(warp == 0 && i == 12, 117);
            }
        }
        PROF_EXIT();
        return;
    }

    if (warp >= 10) {
        if (elect()) {
            if (warp == 10) { _Pragma("unroll") for (int i = B_XF; i < 47; i++) mbar_init(BAR(i), bar_count(i)); }
            else { _Pragma("unroll") for (int i = 47; i < NBARS; i++) mbar_init(BAR(i), bar_count(i)); }
            asm volatile("fence.mbarrier_init.release.cluster;" ::: "memory");
        }
        if (lane < 24) sts128(sb + PB - (warp & 1) * 32768 + (lane & 3) * PP + 4096 + (lane >> 2) * 16, 0, 0, 0, 0);
        if (lane < 12) sts128(sb + (lane < 5 ? HS + lane * XP : lane < 7 ? HO + (lane - 5) * XP : x_at(lane - 7) + 4096), 0, 0, 0, 0);
        fence_async_smem();
    }
    if (warp == 9) bar_arrive(0, 384); else bar_sync(0, 384);
    if (warp == 10) bar_arrive(3, 64);
    STAMPIF(warp == 0, 192);
    asm volatile("barrier.cluster.arrive.relaxed.aligned;" ::: "memory");
    STAMPIF(warp == 0, 6);

    if (warp < 8) {
        const int wg = warp >> 2, w = warp & 3;
        const int q = lane & 3, rr = lane >> 2;
        const bool l0 = lane == 0;
        asm volatile("setmaxnreg.inc.sync.aligned.u32 224;");
        asm volatile("barrier.cluster.wait.aligned;" ::: "memory");
        {
        const int t7 = __shfl_sync(~0u, tid & 127, lane), ln = t7 & 31;
        uint32_t ffp;
        asm("mapa.shared::cluster.u32 %0, %1, %2;" : "=r"(ffp) : "r"(BAR(B_FF)), "r"(rank ^ (ln & 1)));
        uint32_t fa[64];
        auto odd_copy = [&](int n) {
            const uint32_t src = sb + HS + 16 + n * XP + t7 * 16, dst = sb + HO + 16 + wg * XP + t7 * 16;
            uint32_t dr;
            asm volatile("ld.shared.u16 %0, [%1];" : "=r"(dr) : "r"(sb + DS + (bc + 128 * n) * 2) : "memory");
            mbar_wait(BAR(B_H + n), 0);
            STAMPIF(w == 0, 140 + n);
            uint4 v = lds128(src); const uint4 u = lds128(src + 2048);
            const uint32_t pv = lds32(src - 4), pu = lds32(src + 2044);
            if (t7 == 0) { v.x = hadd2(v.x, dr); sts32(src, v.x); }
            sts128(dst, prmt(pv, v.x, 0x5432), prmt(v.x, v.y, 0x5432), prmt(v.y, v.z, 0x5432), prmt(v.z, v.w, 0x5432));
            sts128(dst + 2048, prmt(pu, u.x, 0x5432), prmt(u.x, u.y, 0x5432), prmt(u.y, u.z, 0x5432), prmt(u.z, u.w, 0x5432));
        };
        auto frags = [&](int n, auto I0, auto I1) {
            const uint32_t a = sb + 16 + ((ln & 4) ? HO + wg * XP : HS + n * XP) + 32 * w + 4 * (ln & 3) - 4 * (ln >> 3);
            #pragma unroll
            for (int i = I0.value; i < I1.value; i++) fa[i] = lds32(a + (i >> 2) * 256 + (i & 1) * 128 + (i & 2) * 8);
        };
        using I0 = std::integral_constant<int, 0>; using IA = std::integral_constant<int, FA>; using I64 = std::integral_constant<int, 64>;
        epoch = (epoch >> 7) + 1;
        if (wg) mbar_wait(BAR(B_KV), 0);
        uint32_t list = P.s.wl[wg];
        _Pragma("unroll 1") for (int r = wg; r < 5; r += 2) {
            _Pragma("unroll 1") for (; list; list >>= 4) {
                const int n = (list & 15) - 1;
                if (n < 5) {
                    const int blk = ln & 7, ch = 128 * n + 32 * cg + 2 * (t7 >> 3);
                    uint32_t ka[8], sa = sb + SHT + ch * 8;
                    #pragma unroll
                    for (int i = 0; i < 4; i++) { ka[i] = (sb + kv_at(n) + blk * 64 + (t7 >> 3) * 4) ^ ((blk * 8 + i * 8) & 0x30); ka[i + 4] = ka[i] ^ 0x20; }
                    char* dst = SC(kvT, ch * 4096 + (8 * tb + 7 - blk) * 16);
                    void* hp = CNT(C_KV + 4 * n + cg + 32 * (ln & 1));
                    #pragma unroll
                    for (int i = 0; i < 8; i++) asm volatile("" : "+r"(ka[i]));
                    asm volatile("" : "+r"(sa), "+l"(dst));
                    mbar_wait(BAR(B_KV + n), 0);
                    STAMPIF(w == 0, 195 + n);
                    const uint4 sw = lds128(sa);
                    uint32_t kr[11], o[8];
                    #pragma unroll
                    for (int i = 0; i < 11; i++) { const int row = i < 3 ? 9 * (i + 5) : 9 * (i - 3) + 1; kr[i] = lds32(ka[row & 7] + row * 64); }
                    #pragma unroll
                    for (int i = 0; i < 8; i++) o[i] = lds32(ka[0] + 4608 + i * 512);
                    const uint32_t w0 = prmt(sw.x, sw.z, 0x5410), w1 = prmt(sw.x, sw.z, 0x7632), w2 = prmt(sw.y, sw.w, 0x5410), w3 = prmt(sw.y, sw.w, 0x7632);
                    #pragma unroll
                    for (int i = 0; i < 8; i++) o[i] = hmul2(o[i], hfma2(kr[i + 3], w0, hfma2(kr[i + 2], w1, hfma2(kr[i + 1], w2, hmul2(kr[i], w3)))));
                    stg_tag2<4096>(dst, prmt(o[7], o[6], 0x5410), prmt(o[5], o[4], 0x5410), prmt(o[3], o[2], 0x5410), prmt(o[1], o[0], 0x5410),
                                   prmt(o[7], o[6], 0x7632), prmt(o[5], o[4], 0x7632), prmt(o[3], o[2], 0x7632), prmt(o[1], o[0], 0x7632), epoch);
                    if (w) bar_arrive(10 + n, 128);
                    else {
                        if (n < 2) mbar_wait(BAR(B_CR), 0);
                        bar_sync(10 + n, 128);
                        hint_cnt(hp, ln < 2);
                        pre_add(sb + PRE + ((ln & 1) ? 80 : n * 8), ln < 2);
                        mbar_arrive_remote_if(ffp + 8, ln < 2 && n >= 3);
                        STAMP(n);
                    }
                } else {
                    odd_copy(wg);
                    bar_sync(5 + wg, 128);
                    frags(wg, I0{}, I64{});
                    STAMPIF(w == 0, 145 + r);
                }
            }
            float acc[128];
            const uint32_t xa = sb + x_at(r), pb = sb + PB - wg * 32768, nx = BAR(r == 4 ? B_GO : B_XF + 1 + r);
            uint32_t db = dlo(xa, 16);
            list = P.s.wl[r + 2];
            pre_add(sb + PRE + 88, ln == 0 && r >= 3);
            asm volatile("" : "+r"(db));
            mbar_wait(BAR(B_XF + r), 0);
            STAMPIF(w == 0, 8 + r * 3); GSTAMPIF(w == 0 && r == 0, 106);
            _Pragma("unroll 1") for (int tries = 0;; tries++) {
                wg_fence();
                ConvR<0>::run(acc, fa, db);
                wg_commit();
                mbar_arrive_if(nx, ln == 0 && !tries);
                uint32_t bad = (lds32(xa + t7 * 16) ^ epoch) | (lds32(xa + t7 * 16 + 2048) ^ epoch);
                if (r < 3 && !tries) odd_copy(r + 2);
                wg_wait<0>();
                pin<128>(acc);
                asm volatile("{ .reg .pred p; setp.ne.b32 p, %1, 0; barrier.red.or.pred.aligned p, %2, 128, p; selp.u32 %0, 1, 0, p; }" : "=r"(bad) : "r"(bad & 1), "r"(5 + wg) : "memory");
                if (!bad || tries) break;
                _Pragma("unroll 1") for (int h = 0; h < 4096; h += 2048) {
                    const uint4 v = ldg_tag(SC(kvT, (bc + 128 * r) * 4096 + t7 * 16 + h), epoch);
                    sts128(xa + t7 * 16 + h, v.x, v.y, v.z, v.w);
                }
                fence_async_smem();
                bar_sync(5 + wg, 128);
                STAMP(121);
            }
            STAMPIF(w == 0, 9 + r * 3);
            const uint32_t pw = pb + w * PP + ln * 16;
            #pragma unroll
            for (int g = 0; g < 8; g++) {
                uint32_t o[4];
                #pragma unroll
                for (int l = 0; l < 4; l++) { const int i = 4 * g + l;
                    o[l] = i < 31 ? pack2(acc[4 * i] + acc[4 * i + 6], acc[4 * i + 1] + acc[4 * i + 7]) : pack2(acc[4 * i], acc[4 * i + 1]); }
                asm volatile("stmatrix.sync.aligned.m8n8.x4.trans.shared.b16 [%0], {%1,%2,%3,%4};" :: "r"(pw + g * 512), "r"(o[0]), "r"(o[1]), "r"(o[2]), "r"(o[3]) : "memory");
            }
            char* yp = SC(yB, ((r * 4 + (bc >> 5)) * 32 + (t7 >> 3)) * 4096 + (bc & 31) * 128 + (((t7 & 7) ^ ((bc & 1) << 2)) << 4));
            void* hp = CNT(C_Y + 4 * r + (bc >> 5) + 32 * (ln & 1));
            asm volatile("" : "+l"(yp));
            if (FA && r < 3) frags(r + 2, I0{}, IA{});
            bar_sync(5 + wg, 128);
            uint4 p[2][4];
            #pragma unroll
            for (int h = 0; h < 2; h++)
            #pragma unroll
            for (int k = 0; k < 4; k++) p[h][k] = lds128(pb + (t7 + 128 * h) * 16 + k * (PP + 32));
            uint32_t y[8];
            #pragma unroll
            for (int j = 0; j < 8; j++) y[j] = hadd2((&p[j >> 2][0].x)[j & 3], hadd2((&p[j >> 2][1].x)[j & 3], hadd2((&p[j >> 2][2].x)[j & 3], (&p[j >> 2][3].x)[j & 3])));
            stg_tag2<65536>(yp, y[0], y[1], y[2], y[3], y[4], y[5], y[6], y[7], epoch);
            if (w) {
                bar_arrive(8 + wg, 128);
                const uint32_t pn = (P.s.pw >> (6 * r + 3 * (w & 1))) & 7;
                if (w > 1 && pn && elect()) { pf_l2(padd(P.Wg, (128 * pn - 128 + b) * 3072), 3072); pf_l2(padd(P.Wu, (128 * pn - 128 + b) * 3072), 3072); }
            } else {
                bar_sync(8 + wg, 128);
                hint_cnt(hp, ln < 2);
                pre_add(sb + PRE + 40 + r * 8 + (ln & 1) * 32, ln == 0 || (ln == 1 && r == 3));
                mbar_arrive_remote_if(ffp, ln < 2 && r == (int)P.s.d_w);
                STAMP(10 + r * 3);
            }
            if (r < 3) { frags(r + 2, IA{}, I64{}); STAMPIF(w == 0, 147 + r); }
        }
        }
        if (wg) mbar_wait(BAR(B_GO), 0);
        float acc1[128];
        unsigned long long sv[2] = {};
        const char* s2p = SC(st2, (((tile * 2 + wg) * 4 + q) * 64 + 63 - 16 * (rr >> 1) - (rr & 1) - 4 * w) * 8);
        const uint32_t tag = epoch;
        uint32_t g2e;
        asm("mapa.shared::cluster.u32 %0, %1, %2;" : "=r"(g2e) : "r"(BAR(lane == 2 ? B_HE - 3 : B_G2E)), "r"(rank ^ (lane & 1)));
        const bool l01 = lane < 2;
        const uint32_t wre = g2e - 8 * (B_G2E - B_WE);
        uint32_t p1a = dlo(sb + wg * 8192, 2048), p1s = 0;
        auto pass1 = [&](int k0, int k1, auto&& top, auto&& mid) {
            _Pragma("unroll 1") for (int kb = k0; kb < k1; kb++) {
                top(kb);
                const uint32_t so = p1s & 16, db = dlo(sb + WR, 4096) + so * 128;
                mbar_wait(BAR(B_AF) + kb * 8, 0);
                #pragma unroll
                for (int h = 0; h < 2; h++) {
                    mbar_wait(BAR(B_WF + h) + so, p1s >> 31);
                    STAMPIF(kb + h == 0 && w == 0, 24 + wg);
                    GSTAMPIF(kb + h == 0 && warp == 0, 107);
                    STAMPIF(warp == 0, 64 + 2 * kb + h);
                    wg_fence();
                    WG<256>::ss<1, 1>(acc1, p1a + h * 256, dhi(512, 2), db + h * 1024, dhi(1024, 1), (h || k0) ? 1 : kb);
                    mid(h, kb);
                    WG<256>::ss<1, 1>(acc1, p1a + h * 256 + 64, dhi(512, 2), db + h * 1024 + 128, dhi(1024, 1), 1);
                    wg_commit();
                    wg_wait<1>();
                    mbar_arrive_remote_if(wre + (h ? so : (so ^ 16) + 8), l01 && (kb + h) > 0);
                }
                p1a += 1024; p1s = (p1s ^ 16) + (so << 27);
            }
        };
        uint32_t ax[4];
        float acc2[64];
        float rq0, rq1, e0, e1, f0, f1;
        uint32_t m0, m1, d0, d1, stale;
        auto st_load = [&](bool p) {
            #pragma unroll
            for (int i = 0; i < 2; i++)
                asm volatile("{ .reg .pred p; setp.ne.b32 p, %2, 0; @p ld.relaxed.gpu.global.b64 %0, [%1]; }" : "+l"(sv[i]) : "l"(s2p - i * 16), "r"((int)p) : "memory");
        };
        auto st_step = [&](int n) {
            if (n == 0) {
                stale = (((uint32_t)sv[0] ^ tag) | ((uint32_t)sv[1] ^ tag)) & 7;
                const float a0 = __uint_as_float((uint32_t)sv[0]), b0 = __uint_as_float(sv[0] >> 32), a1 = __uint_as_float((uint32_t)sv[1]), b1 = __uint_as_float(sv[1] >> 32);
                e0 = (q & 1) ? b0 : a0; e1 = (q & 1) ? b1 : a1;
                f0 = __shfl_xor_sync(~0u, (q & 1) ? a0 : b0, 1); f1 = __shfl_xor_sync(~0u, (q & 1) ? a1 : b1, 1);
            } else if (n < 3) {
                e0 += f0; e1 += f1;
                f0 = __shfl_xor_sync(~0u, e0, 3 - n); f1 = __shfl_xor_sync(~0u, e1, 3 - n);
            } else {
                const float mu0 = ((q & 1) ? f0 : e0) * (1.f / D_), mu1 = ((q & 1) ? f1 : e1) * (1.f / D_);
                const float ve0 = fmaxf(((q & 1) ? e0 : f0) * (1.f / D_) - mu0 * mu0, 0.f) + 1e-5f, ve1 = fmaxf(((q & 1) ? e1 : f1) * (1.f / D_) - mu1 * mu1, 0.f) + 1e-5f;
                asm("rsqrt.approx.ftz.f32 %0, %1;" : "=f"(rq0) : "f"(ve0)); asm("rsqrt.approx.ftz.f32 %0, %1;" : "=f"(rq1) : "f"(ve1));
                d0 = split2(ve0 * rq0); d1 = split2(ve1 * rq1); m0 = split2(-mu0); m1 = split2(-mu1);
                rq0 *= rq0; rq1 *= rq1;
                asm volatile("" : "+r"(d0), "+r"(d1), "+r"(m0), "+r"(m1) :: "memory");
            }
        };
        pass1(0, 9, [&](int kb) {
            if (kb == KB_UT) {
                float au[4];
                const int t3 = (tile * 11) >> 5, cn = 2 * (tile - 3 * t3) + wg;
                mbar_wait(BAR(B_UF), 0);
                STAMPIF(warp == 0, 33);
                const uint32_t ua = dlo(sb + UST + wg * 16384, 16), ub = dlo(sb + CS_TAB, 32);
                char* up = SC(ut, (t3 * 3072 + (cn >= 3) * 1344 + js * 192 + cn * 64 + w * 16 + rr) * 8);
                wg_fence();
                #pragma unroll
                for (int ks = 0; ks < 8; ks++) WG<8>::ss<1, 0>(au, ua + ks * 128, dhi(1024, 1), ub + ks * 4, dhi(128, 0), ks != 0);
                wg_commit();
                wg_wait<0>();
                pin<4>(au);
                pre_add(sb + PRE + 104, l0);
                asm volatile("{ .reg .pred p; .reg .b64 x; setp.eq.b32 p, %5, 0; mov.b64 x, {%1, %2}; @p st.relaxed.gpu.global.b64 [%0], x; mov.b64 x, {%3, %4}; @p st.relaxed.gpu.global.b64 [%0+64], x; }"
                             :: "l"(up), "r"(tagged(au[0], tag)), "f"(au[1]), "r"(tagged(au[2], tag)), "f"(au[3]), "r"(q | (tile == 15)) : "memory");
                mbar_arrive_if(BAR(B_UD), l0);
                STAMPIF(warp == 0, 60);
            }
        }, [&](int h, int kb) { if (h == 0) st_load(kb == 8); });
        pass1(9, 10, [&](int) { st_step(0); }, [&](int h, int) { if (h == 0) { st_step(1); st_step(2); } else st_step(3); });
        _Pragma("unroll 1") for (int it = 0; it < 20000 && __any_sync(~0u, stale != 0); it++) { st_load(true); st_step(0); st_step(1); st_step(2); st_step(3); }
        {
            const uint32_t zm = q == 0 ? ~0u : q == 1 ? 0xffffu : 0u, sh = q ? 0x5454 : 0x5410, sl = sh + 0x2222;
            ax[0] = prmt(m0, d0, sh) & zm; ax[1] = prmt(m1, d1, sh) & zm; ax[2] = prmt(m0, d0, sl) & zm; ax[3] = prmt(m1, d1, sl) & zm;
            asm volatile("" : "+r"(ax[0]), "+r"(ax[1]), "+r"(ax[2]), "+r"(ax[3]) :: "memory");
        }
        {
            mbar_wait(BAR(B_T1), 0);
            wg_fence();
            WG<256>::rs<1>(acc1, ax[0], ax[1], ax[2], ax[3], dlo(sb + TAB1, 0), dhi(48, 0), 1);
            WG<128>::rs<1>(acc2, ax[0], ax[1], ax[2], ax[3], dlo(sb + TAB2, 0), dhi(48, 0), 0);
            wg_commit();
        }
        char* hdst = SC(hh, (tile * 24 + js * 3) * 16384 + wg * 8192 + w * 2048 + q * 128 + rr * 16);
        wg_wait<1>();
        mbar_arrive_remote_if(wre + 24, l01);
        STAMPIF(w == 0, 26 + wg);
        GSTAMPIF(warp == 0, 108);
        uint32_t hq[48];
        static_for<0, 10>([&](auto IT) {
            constexpr int it = IT.value;
            STAMPIF(warp == 0, 236 + it);
            mbar_wait(BAR(w2_bar(it)), it < 4);
            STAMPIF(warp == 0, 84 + it);
            const uint32_t da = dlo(sb + it * 16384 + wg * 8192, 2048), db = dlo(sb + w2_at(it), 8192);
            wg_fence();
            static_for<0, 4>([&](auto KS) {
                constexpr int ks = KS.value;
                WG<128>::ss<1, 1>(acc2, da + (ks >> 1) * 256 + (ks & 1) * 64, dhi(512, 2), db + ks * 128, dhi(1024, 1), 1);
                if constexpr (ks == 0) {
                    wg_commit();
                    wg_wait<1>();
                    if (it == 0) pin<128>(acc1);
                    if ((it > 0 && it < 6) || it == 7) mbar_arrive_remote_if(wre + 8 * (it == 7 ? 1 : (it + 3) & 3), l01);
                    static_for<0, 6>([&](auto G) { if constexpr (((B2S >> (4 * G.value)) & 15) == it) mbar_arrive_remote_if(g2e + 8 * G.value, l01); });
                }
                static_for<0, 8>([&](auto PP_) {
                    constexpr int hs = (HPS >> (4 * PP_.value)) & 15;
                    if constexpr (PP_.value == 2 * it + ks && ks < 2) ffn_epi<7 - PP_.value, false>(acc1, acc1 + 64, rq0, rq1, hq, hdst, tag);
                    if constexpr (hs == 2 * it + ks && ks < 2) hh_store<7 - PP_.value>(hq, hdst);
                    if constexpr ((PP_.value & 3) == 3 && (hs >> 1) == it && ks == 3) { __syncwarp(); mbar_arrive_if(BAR(PP_.value == 3 ? B_HD : B_HD + 1), l0); }
                });
            });
            wg_commit();
        });
        STAMPIF(w == 0, 30 + wg);
        {
            float acc[80];
            static_for<0, 3>([&](auto IT) {
                constexpr int it = IT.value;
                mbar_wait(BAR(B_G2F + it), 0);
                STAMPIF(w == 0 && it == 0, 34 + wg);
                STAMPIF(warp == 0, 94 + it);
                const uint32_t db = dlo(sb + g2b_at(it), 2048);
                #pragma unroll
                for (int i = 0; i < 16; i++) asm volatile("" : "+r"(hq[16 * it + i]) :: "memory");
                wg_fence();
                #pragma unroll
                for (int ks = 0; ks < 4; ks++) {
                    const uint32_t* o = hq + 16 * it + 8 * (ks >> 1) + 2 * (ks & 1);
                    WG<160>::rs<1>(acc, o[0], o[4], o[1], o[5], db + (ks >> 1) * 640 + (ks & 1) * 64, dhi(512, 2), it != 0 || ks != 0);
                    if (it == 0 && ks == 1) {
                        wg_commit();
                        wg_wait<1>();
                        pin<64>(acc2);
                        mbar_arrive_if(BAR(B_S0), l0);
                        static_for<0, 6>([&](auto G) { if constexpr (((B2S >> (4 * G.value)) & 15) == 10) mbar_arrive_remote_if(g2e + 8 * G.value, l01); });
                        ffn_epi<0>(acc2, acc2 + 32, rq0, rq1, hq + 32, hdst + 32768, tag);
                        wg_fence();
                    }
                    if (it == 1 && ks == 0) ffn_epi<2>(acc2, acc2 + 32, rq0, rq1, hq + 32, hdst + 32768, tag);
                    if (it == 1 && ks == 1) { ffn_epi<3>(acc2, acc2 + 32, rq0, rq1, hq + 32, hdst + 32768, tag); __syncwarp(); mbar_arrive_if(BAR(B_HD), l0); }
                }
                wg_commit();
                if (it == 0) ffn_epi<1>(acc2, acc2 + 32, rq0, rq1, hq + 32, hdst + 32768, tag);
                else {
                    wg_wait<1>();
                    mbar_arrive_remote_if(g2e + 8 * (it ? it - 1 : 0), l01);
                }
            });
            _Pragma("unroll 1") for (int it = 3; it < 12; it++) {
                const int g = it >= 6 ? it - 6 : it, ga = (0x325104 >> (4 * g)) & 7;
                if (it == 9 && wg == 1) bar_sync(7, 256);
                mbar_wait(BAR(B_G2F + g), it >= 6);
                mbar_wait(BAR(B_AF - 3 + it), 1);
                STAMPIF(w == 0 && it == 9, 36 + wg);
                STAMPIF(warp == 0, 94 + it);
                const uint32_t da = dlo(sb + G2A + ga * 16384 + wg * 8192, 128), db = dlo(sb + g2b_at(g), 2048);
                wg_fence();
                #pragma unroll
                for (int ks = 0; ks < 4; ks++) WG<160>::ss<0, 1>(acc, da + ks * 16, dhi(1024, 0), db + (ks >> 1) * 640 + (ks & 1) * 64, dhi(512, 2), 1);
                wg_commit();
                if (it == 11 && wg == 0) bar_arrive(7, 256);
                wg_wait<1>();
                mbar_arrive_remote_if(g2e + 8 * (it - 1), lane < 2 + (it > 3) && it < 7);
            }
            mbar_wait(BAR(B_X1), 0);
            uint32_t gw[20];
            #pragma unroll
            for (int i = 0; i < 5; i++) { const uint4 g = lds128(sb + GBT + q * 80 + i * 16); gw[4 * i] = g.x; gw[4 * i + 1] = g.y; gw[4 * i + 2] = g.z; gw[4 * i + 3] = g.w; }
            bar_sync(5 + wg, 128);
            uint32_t osts[2];
            const uint32_t orow = (15 - (lane & 15)) * 160 + (lane >> 4) * 16;
            #pragma unroll
            for (int hf = 0; hf < 2; hf++) { const int pc = 2 * w + hf, p3 = (pc * 11) >> 5; osts[hf] = sb + G2A + p3 * p3 * 16384 + wg * 8192 + (pc - 3 * p3) * 2560; }
            wg_wait<0>();
            pin<80>(acc);
            STAMPIF(w == 0, 38 + wg);
            GSTAMPIF(warp == 0, 109);
            #pragma unroll
            for (int i = 0; i < 10; i++) {
                uint32_t o[4];
                #pragma unroll
                for (int j = 0; j < 4; j++) { const int n = 4 * i + j; o[j] = hmul2(pack2(acc[2 * n], acc[2 * n + 1]), gw[n >> 1]); }
                asm volatile("stmatrix.sync.aligned.m8n8.x4.shared.b16 [%0], {%1,%2,%3,%4};" :: "r"(osts[i / 5] + orow + (i % 5) * 32), "r"(o[0]), "r"(o[1]), "r"(o[2]), "r"(o[3]) : "memory");
            }
            fence_async_smem();
            __syncwarp();
            STAMPIF(w == 0, 123 + wg);
            if (elect()) {
                fence_async_glob();
                tma2d_red(&M.out, osts[0], dq * 160, S_ - 128 * tile - 16 * warp - 16);
                tma2d_red(&M.out, osts[1], dq * 160 + 80, S_ - 128 * tile - 16 * warp - 16);
                asm volatile("cp.async.bulk.commit_group;\n cp.async.bulk.wait_group.read 0;" ::: "memory");
            }
            STAMPIF(w == 0, 42 + wg);
            GSTAMPIF(warp == 0, 47);
        }
        PROF_EXIT();
    } else {
        asm volatile("setmaxnreg.dec.sync.aligned.u32 56;");
        if (warp == 8) {
            const int r = pr;
            const char* src = kind == 0 ? SC(kvT, (bc + 128 * r) * 4096) : kind == 1 ? SC(yB, ((r * 4 + cg) * 32 + tb) * 4096) : SC(z, (tile * 10 + lane - 20) * 16384);
            const uint32_t dst = sb + (kind == 0 ? x_at(r) : kind == 1 ? YS + (r - 3 * (r >= 3)) * 4096 : (lane - 20) * 16384);
            const uint32_t bytes = kind == 2 ? 16384 : 4096, full = BAR(kind == 2 ? B_KV - 20 + lane : B_XF + (lane >> 1)), pre = sb + PRE + (lane >> 1) * 8, slot = sb + PS + lane * 16;
            uint32_t need = lane >= 30 ? ~0u : lane < 16 ? 0 : (0x1a3a722 >> (2 * (lane & 14))) & 15;
            const uint32_t lbit = __shfl_sync(~0u, (kind == 2 || (kind < 2 && !(lane & 1))) ? 1u << lane : 0u, lane), pbit = __shfl_sync(~0u, 3u << (lane & 30), lane);
            uint32_t todo = 0x15555555, it = 0;
            if (lbit && kind < 2) mbar_expect(full, bytes);
            asm volatile("cp.async.wait_all;" ::: "memory");
            const uint32_t goal = (lds32(slot) | 127) + 1;
            if (lane == 31) sts32(sb + HT, goal);
            __syncwarp();
            mbar_arrive_if(BAR(B_CR), lane == 0);
            STAMP(5);
            const int tl = tile - (tile == 15), t3 = (tl * 11) >> 5, cn = 2 * (tl - 3 * t3);
            if (lane == 0) mbar_expect(BAR(B_UF), 32768);
            auto load_w = [&](int m) {
                const uint32_t f = BAR(B_WF + (m & 3));
                mbar_expect(f, 16384);
                tma3d_mc(sb + WR + (m & 3) * 16384 + rank * 8192, &M.w[0] + rank, m * 32, js * 3, f);
                if (m == 12) pf_l2(padd(P.Wd, b * 15360), 15360);
                if ((m >> 2) == 1) {
                    const int cm = cn + ((m >> 1) & 1);
                    tma3d(sb + UST + (m & 3) * 8192, cm >= 3 ? &M.w[3] : &M.w[2], 0, t3 * 128 + (m & 1) * 64, js * 3 + cm - 3 * (cm >= 3), BAR(B_UF));
                }
            };
            int m = 0;
            __syncwarp();
            while (todo) {
                uint32_t hit, due;
                asm volatile("{ .reg .pred p, t; .reg .u32 c, v;\n LAB_EV:\n ld.volatile.shared.u32 c, [%5]; ld.volatile.shared.u32 v, [%3];\n"
                             " mbarrier.test_wait.parity.shared::cta.b64 t, [%7], %8; add.u32 %2, %2, 1;\n"
                             " setp.gt.u32 p, c, %6; @p cp.async.cg.shared.global [%3], [%4], 16; sub.u32 v, v, %9; setp.ge.and.s32 p, v, 0, p; setp.ge.or.u32 p, %2, 400000, p;\n"
                             " vote.sync.ballot.b32 %0, p, 0xffffffff; setp.ne.or.u32 p, %0, 0, t;\n @!p bra.uni LAB_EV;\n vote.sync.ballot.b32 %1, t, 0xffffffff; }"
                             : "=r"(hit), "=r"(due), "+r"(it) : "r"(slot), "l"(cp), "r"(pre), "r"(need), "r"(BAR(m < 4 ? B_FF + (m >> 1) : B_WE + (m & 3))), "r"(m < 4 ? 0 : ~(m >> 2) & 1), "r"(goal) : "memory");
                if (due) { if (elect()) load_w(m); m++; }
                if (hit) {
                    STAMPL(!(lane & 1) && (hit & pbit) && lane < 30, 216 + (lane >> 1));
                    if (hit & pbit) { need = ~0u; if (kind == 2) mbar_expect(full, 16384); if (lbit) bulk_g2s(dst, src, bytes, full); }
                    todo &= ~(hit | (hit >> 1));
                    __syncwarp();
                }
            }
            asm volatile("cp.async.wait_all;" ::: "memory");
            __syncwarp();
            if (elect()) {
                mbar_arrive(BAR(B_UD));
                _Pragma("unroll 1") for (; m < 20; m++) { mbar_wait(BAR(B_WE + (m & 3)), ~(m >> 2) & 1); load_w(m); }
                #pragma unroll
                for (int it = 0; it < 10; it++) {
                    if (it < 4 || !(it & 1)) mbar_wait(BAR(B_WE + (it < 4 ? it : (it >> 1) - 2)), it >= 4);
                    STAMP(246 + it);
                    mbar_expect(BAR(w2_bar(it)), 16384);
                    tma3d_mc(sb + w2_at(it) + rank * 8192, &M.w[2] + rank, it * 64, js * 3 + 2, BAR(w2_bar(it)));
                }
                #pragma unroll
                for (int m = 0; m < 9; m++) mbar_expect(BAR(B_KV + m), 16384);
                const char* hp[3];
                #pragma unroll
                for (int m = 0; m < 3; m++) hp[m] = SC(hh, (tile * 24 + (kh * 4 + m + (m >= dq)) * 3) * 16384);
                const uint32_t* fl = CNT(C_HH + tile * 2 + kh);
                const uint32_t target = lds32(sb + HT);
                sts128(sb + TAB1, target - 1, target - 1, target - 1, 0); sts128(sb + TAB1 + 16, target - 1, target - 1, target - 1, 0);
                #pragma unroll
                for (int c = 0; c < 3; c++) {
                    poll_dual(fl, sb + TAB1, 4 * c, target);
                    STAMP(170 + c);
                    if (c == 1) mbar_wait(BAR(B_S0), 0);
                    #pragma unroll
                    for (int m = 0; m < 3; m++) {
                        if (c == 0) mbar_wait(BAR(B_WE + ((m + 3) & 3)), m == 0);
                        if (c == 2) mbar_wait(BAR(B_HE + m), 0);
                        bulk_g2s(sb + G2A + ((c & 1) ? (m ? m - 1 : 4) : m ? m + 1 : 5) * 16384, hp[m] + (c ^ (c < 2)) * 16384, 16384, BAR(B_KV + 3 * c + m));
                    }
                }
                asm volatile("cp.async.wait_all;" ::: "memory");
            }
            PROF_EXIT();
            return;
        }
        uint32_t rtp = 0;
        auto validate = [&](int v, uint32_t par, uint32_t dst, uint32_t src) {
            const uint32_t a = sb + dst + (lane >> 3) * 516 + (lane & 7) * 16;
            mbar_wait(BAR(B_KV + v), par);
            _Pragma("unroll 1") for (int it = 0; it < 1000; it++) {
                uint32_t w[32], bad = 0;
                #pragma unroll
                for (int i = 0; i < 32; i++) w[i] = lds32(a + (i >> 2) * 2048 + (i & 3) * 128);
                #pragma unroll
                for (int i = 0; i < 32; i += 4)
                    asm("{ .reg .b32 a, b; lop3.b32 a, %1, %2, %5, 0x7e; lop3.b32 b, %3, %4, %5, 0x7e; lop3.b32 %0, %0, a, b, 0xfe; }" : "+r"(bad) : "r"(w[i]), "r"(w[i + 1]), "r"(w[i + 2]), "r"(w[i + 3]), "r"(epoch));
                if (!__any_sync(~0u, bad & 1)) break;
                if (elect()) { mbar_expect(BAR(B_RT), 16384); bulk_g2s(sb + dst, padd(P.scr, src), 16384, BAR(B_RT)); }
                mbar_wait(BAR(B_RT), rtp);
                rtp ^= 1;
                STAMP(122 - 4 * par);
            }
            mbar_arrive_if(BAR(B_AF + v), lane == 0);
        };
        if (warp == 9) {
            auto pf_w = [&](int r) { pf_l2(padd(P.Wg, (128 * r + b) * 3072), 3072); pf_l2(padd(P.Wu, (128 * r + b) * 3072), 3072); };
            if (elect()) {
                pf_map(&M.q);
                _Pragma("unroll 1") for (int i = 0; P.s.ld[i]; i++) {
                    const uint32_t e = P.s.ld[i], n = e & 15;
                    if (e & 32) {
                        if (e & 16) { wait_clock(clk0, e >> 8); pf_w(n); }
                        else { mbar_expect(BAR(B_Q + n), 4096); wait_clock(clk0, e >> 8); tma4d(sb + QS + n * 4096, &M.q, n * 128 + cg * 32, 248 - 8 * tb, BAR(B_Q + n)); }
                    } else if (e & 16) { mbar_expect(BAR(B_H + n), 4096); wait_clock(clk0, e >> 8); load_h(n); }
                    else { mbar_expect(BAR(B_KV + n), KVP); wait_clock(clk0, e >> 8); load_kv(n); }
                }
                STAMP(126);
            }
            bar_sync(3, 64);
            mbar_wait(BAR(B_CR), 0);
            epoch = lds32(sb + HT) >> 7;
            _Pragma("unroll 1") for (int v = 0; v < 10; v++) mbar_wait(BAR(B_KV + v), 0);
            pre_add(sb + PRE + 80 + lane * 8, lane < 5);
            _Pragma("unroll 1") for (int v = 0; v < 10; v++) {
                validate(v, 1, v * 16384, offsetof(Scratch, z) + (tile * 10 + v) * 16384);
                STAMPIF(!(v & 1), 165 + (v >> 1));
                if (v == (int)P.s.g_w) {
                    float2 sc[4];
                    ll_read2<2, 5120, 2, 512>(SC(mod, (1920 + (((tile - (tile == 15)) * 11) >> 5) * 128 + 2 * lane) * 8), epoch, sc);
                    #pragma unroll
                    for (int n = 0; n < 4; n++) { const float one = n >> 1;
                        sts32(sb + CS_TAB + ((lane >> 2) + 8 * (n & 1)) * 32 + (lane & 3) * 4 + (n < 2) * 16, pack2(bfround(sc[n].x) + one, bfround(sc[n].y) + one)); }
                    fence_async_smem(); __syncwarp(); mbar_arrive_if(BAR(B_UF), lane == 0);
                    STAMP(52);
                }
            }
        } else {
            mbar_wait(BAR(B_CR), 0);
            epoch = lds32(sb + HT) >> 7;
            if (warp == 11 && elect()) { pf_map(&M.w[0]); pf_map(&M.w[1]); pf_map(&M.o1); pf_map(&M.w[2]); pf_map(&M.w[3]); pf_map(&M.wd); pf_map(&M.wn); pf_map(&M.out); }
            const int wf = warp - 10, c = lane >> 2, run = 4 * wf + (lane & 3);
            auto mod_load = [&](uint2* mv, int r, int lane) {
                const char* mp = SC(mod, (128 * r + 32 * cg + lane) * 8);
                #pragma unroll
                for (int i = 0; i < 4; i++) asm volatile("{ .reg .b64 x; ld.relaxed.gpu.global.b64 x, [%2]; mov.b64 {%0, %1}, x; }" : "=r"(mv[i].x), "=r"(mv[i].y) : "l"(mp + (i + (i == 3)) * 5120) : "memory");
            };
            auto mod_put = [&](uint2* mv, int r, int lane) {
                _Pragma("unroll 1") for (int it = 0; it < 20000 && __any_sync(~0u, ((mv[0].y ^ epoch) | (mv[1].y ^ epoch) | (mv[2].y ^ epoch) | (mv[3].y ^ epoch)) != 0); it++) { asm volatile("nanosleep.u32 100;"); mod_load(mv, r, lane); }
                const float ga = bfround(__uint_as_float(mv[2].x)), a0 = ga * bfround(__uint_as_float(mv[0].x)), a1 = ga * bfround(bfround(__uint_as_float(mv[1].x)) + 1.f), c1 = bfround(__uint_as_float(mv[3].x)) + 1.f;
                asm volatile("st.shared.v2.b32 [%0], {%1, %2};" :: "r"(sb + CT + wf * 256 + (lane & 7) * 32 + (lane >> 3) * 8), "r"(pack2(a0, a1)), "r"(pack2(c1, c1)) : "memory");
            };
            const int qrow = 63 - 16 * (lane >> 3) - 8 * wf - (lane & 7);
            uint32_t qa = sb + QS + qrow * 64 + (((qrow >> 1) & 3) << 4);
            float st[4] = {0.f, 0.f, 0.f, 0.f};
            auto row_stats = [&](uint32_t a) {
                uint4 v[4];
                #pragma unroll
                for (int i = 0; i < 4; i++) v[i] = lds128(a ^ (i << 4));
                #pragma unroll
                for (int i = 0; i < 16; i++) {
                    const uint32_t u = (&v[i >> 2].x)[i & 3]; const float a0 = bflo(u), a1 = bfhi(u);
                    vadd(st[0], a0); vfma(st[1], a0, a0); vadd(st[2], a1); vfma(st[3], a1, a1);
                    if ((i & 3) == 3) yield();
                }
            };
            auto put_stats = [&](uint32_t off) { ll_write1(padd(P.scr, off + ((tb * 4 + cg) * 64 + qrow) * 8), __uint_as_float(tagged(st[0] + st[2], epoch)), __float_as_uint(st[1] + st[3])); };
            _Pragma("unroll 1") for (int r = 0; r < 5; r++) { mbar_wait(BAR(B_Q + r), 0); STAMPIF(wf == 0 && r == 4, 62); row_stats(qa + r * 4096); }
            put_stats(offsetof(Scratch, st1));
            st[0] = st[1] = st[2] = st[3] = 0.f;
            STAMPIF(wf == 0, 40);
            pause(P.s.spin);
            {
                const char* sp = SC(st1, (tb * 256 + 63 - 16 * (c >> 1) - (c & 1) - 2 * run) * 8);
                float s, ss;
                uint2 mv[4];
                mod_load(mv, 0, lane);
                _Pragma("unroll 1") for (int it = 0; it < 20000; it++) {
                    uint2 v[4];
                    #pragma unroll
                    for (int i = 0; i < 4; i++) asm volatile("{ .reg .b64 x; ld.relaxed.gpu.global.b64 x, [%2]; mov.b64 {%0, %1}, x; }" : "=r"(v[i].x), "=r"(v[i].y) : "l"(sp + i * 512) : "memory");
                    s = (__uint_as_float(v[0].x) + __uint_as_float(v[1].x)) + (__uint_as_float(v[2].x) + __uint_as_float(v[3].x));
                    ss = (__uint_as_float(v[0].y) + __uint_as_float(v[1].y)) + (__uint_as_float(v[2].y) + __uint_as_float(v[3].y));
                    if (!__any_sync(~0u, (((v[0].x ^ epoch) | (v[1].x ^ epoch) | (v[2].x ^ epoch) | (v[3].x ^ epoch)) & 7) != 0)) break;
                    asm volatile("nanosleep.u32 100;");
                }
                const float mu = s * (1.f / D_), rs = bfround(rsqrtf(fmaxf(ss * (1.f / D_) - mu * mu, 0.f) + 1e-5f));
                const uint32_t mr = pack2(-mu * rs, rs);
                asm volatile("st.shared.u16 [%0], %1; st.shared.u16 [%0+128], %2;" :: "r"(sb + MR + run * 16 + c * 2), "h"((uint16_t)mr), "h"((uint16_t)(mr >> 16)) : "memory");
                STAMPIF(wf == 0, 41);
                mod_put(mv, 0, lane);
            }
            char* zp = SC(z, ((tb >> 1) * 10 + (cg >> 1)) * 16384 + (tb & 1) * 8192 + (cg & 1) * 4096 + wf * 2048 + c * 64 + (((lane ^ (c >> 1)) & 3) << 4));
            _Pragma("unroll 1") for (int r = 0; r < 5; r++) {
                int lane = tid & 31;
                asm volatile("" : "+r"(lane));
                const int c = lane >> 2, run = 4 * wf + (lane & 3);
                const uint32_t ys = sb + YS + (r - 3 * (r >= 3)) * 4096, ya = ys + c * 128 + ((run ^ ((c & 1) << 2)) << 4);
                __syncwarp();
                STAMPIF(wf == 0, 150 + r);
                uint32_t x[16];
                #pragma unroll
                for (int h = 0; h < 4; h++) asm volatile("ldmatrix.sync.aligned.m8n8.x4.trans.shared.b16 {%0,%1,%2,%3}, [%4];" : "=r"(x[4 * h]), "=r"(x[4 * h + 1]), "=r"(x[4 * h + 2]), "=r"(x[4 * h + 3]) : "r"(qa ^ (h << 4)) : "memory");
                const uint4 mu = lds128(sb + MR + run * 16), rs = lds128(sb + MR + 128 + run * 16);
                mbar_wait(BAR(B_YF + r), 0);
                asm volatile("xor.b32 %0, %0, %1;" : "+r"(qa) : "r"(lds32(sb + HT) & 127));
                STAMPIF(wf == 0, 155 + r);
                #pragma unroll
                for (int hh = 0; hh < 4; hh += 2) {
                    uint4 y[2];
                    #pragma unroll
                    for (int h = 0; h < 2; h++) y[h] = lds128(ya + (hh + h) * 1024);
                    const uint4 cs = lds128(sb + CT + wf * 256 + c * 32 + hh * 8);
                    if (((y[0].x ^ epoch) | (y[1].x ^ epoch)) & 1) {
                        #pragma unroll
                        for (int h = 0; h < 2; h++) y[h] = ldg_tag(SC(yB, ((r * 4 + cg) * 32 + tb) * 4096 + (ya - ys) + (hh + h) * 1024), epoch);
                        STAMPL(true, 125);
                    }
                    __syncwarp();
                    #pragma unroll
                    for (int h = hh; h < hh + 2; h++) {
                        uint32_t* xh = x + 4 * h;
                        #pragma unroll
                        for (int j = 0; j < 4; j++)
                            asm("{ .reg .b16 l, h; .reg .b32 a0, a1, n; mov.b32 {l, h}, %3; mov.b32 a0, {l, l}; mov.b32 a1, {h, h}; fma.rn.bf16x2 n, %0, %1, %2; fma.rn.bf16x2 n, n, a1, a0; fma.rn.bf16x2 %0, n, %4, %0; }"
                                : "+r"(xh[j]) : "r"((&rs.x)[j]), "r"((&mu.x)[j]), "r"((h & 1) ? cs.z : cs.x), "r"((&y[h - hh].x)[j]));
                        const uint32_t c1 = (h & 1) ? cs.w : cs.y;
                        uint32_t zo[4] = {hmul2(xh[0], c1), hmul2(xh[1], c1), hmul2(xh[2], c1), hmul2(xh[3], c1)};
                        zo[h] = tagbit(zo[h], epoch);
                        stg_b128(zp + h * 512, zo[0], zo[1], zo[2], zo[3]);
                    }
                }
                __syncwarp();
                hint_cnt<8>(CNT(C_Z + 64 * r + (tb >> 1) + 32 * (lane & 1)), lane < 2);
                pre_add(sb + PRE + 80 + r * 8 - 16 * (lane & 1), lane ? lane == 1 && r < 2 : r < 4);
                STAMPIF(wf == 0, 160 + r);
                #pragma unroll
                for (int h = 0; h < 4; h++) asm volatile("stmatrix.sync.aligned.m8n8.x4.trans.shared.b16 [%0], {%1,%2,%3,%4};" :: "r"(qa ^ (h << 4)), "r"(x[4 * h]), "r"(x[4 * h + 1]), "r"(x[4 * h + 2]), "r"(x[4 * h + 3]) : "memory");
                __syncwarp();
                {
                    uint2 mv[4];
                    mod_load(mv, r + (r < 4), lane);
                    row_stats(qa);
                    mod_put(mv, r + (r < 4), lane);
                }
                fence_async_smem();
                __syncwarp();
                mbar_arrive_if(BAR(B_FD + r), lane == 0);
                if (!wf)
                    _Pragma("unroll 1") for (int xs = (P.s.xd >> (4 * r)) & 7; xs < (int)((P.s.xd >> (4 * r + 4)) & 7); xs++) { mbar_wait(BAR(B_FD + xs), 0); if (elect()) tma4d_st(&M.o1, sb + QS + xs * 4096, xs * 128 + cg * 32, 248 - 8 * tb); }
                qa += 4096; zp += 32768;
            }
            put_stats(offsetof(Scratch, st2));
            if (!wf && elect()) { asm volatile("cp.async.bulk.commit_group;\n cp.async.bulk.wait_group.read 0;" ::: "memory"); pre_add(sb + PRE + 112, true); }
            __syncwarp();
            STAMPIF(wf, 53);
        }
        {
            mbar_wait(BAR(B_UD), 0);
            const int n = warp - 9;
            _Pragma("unroll 1") for (int h = 0; h < 2; h++) {
                const char* up = SC(ut, (h * 1536 + js * 192 + n * 64 + 2 * lane) * 8);
                uint4 v[5];
                _Pragma("unroll 1") for (int it = 0; it < 20000; it++) {
                    uint32_t bad = 0;
                    #pragma unroll
                    for (int i = 0; i < 5; i++) v[i] = ldg_rlx128(up + i * 24576);
                    #pragma unroll
                    for (int i = 0; i < 5; i++) bad |= (v[i].x ^ epoch) | (v[i].z ^ epoch);
                    if (!__any_sync(~0u, (bad & 7) != 0)) break;
                    asm volatile("nanosleep.u32 100;");
                }
                float f[4];
                #pragma unroll
                for (int j = 0; j < 4; j++) f[j] = (__uint_as_float((&v[0].x)[j]) + __uint_as_float((&v[1].x)[j])) + (__uint_as_float((&v[2].x)[j]) + __uint_as_float((&v[3].x)[j])) + __uint_as_float((&v[4].x)[j]);
                const uint32_t ta = sb + TAB1 + ((n == 2 ? 32 + h * 8 : n * 8 + h * 16) + (lane >> 2)) * 48 + (lane & 3) * 4, th2 = pack2(f[1], f[3]);
                sts32(ta, pack2(f[0], f[2])); sts32(ta + 16, th2); sts32(ta + 32, pack2(f[1] - bflo(th2), f[3] - bfhi(th2)));
            }
            if (lane < 20) sts32(sb + TAB1 + 48 * 48 + lane * 4, 0);
            fence_async_smem();
            __syncwarp();
            if (lane == 0) mbar_arrive(BAR(B_T1));
            STAMPIF(warp == 10, 61);
        }
        if (warp == 11) {
            char* hc = paddv(P.scr, (C_HH + tile * 2 + kh + 32 * (lane & 1)) * 128);
            #pragma unroll
            for (int c = 0; c < 3; c++) { mbar_wait(BAR(B_HD + (c & 1)), c >> 1); hint_cnt<32>(hc + 4 * c, lane < 2); STAMP(176 + c); }
            float2 gbv[3];
            ll_read<3, 384>(SC(mod, (5 * 640 + dq * 160 + 2 * lane) * 8), epoch, gbv);
            #pragma unroll
            for (int n = 0; n < 3; n++) sts32(sb + GBT + (lane & 3) * 80 + ((lane >> 2) + 6 * n) * 4, pack2(gbv[n].x, gbv[n].y));
            poll_cnt((uint32_t*)paddv(P.scr, C_ZO * 128 + (lds32(sb + HT) & 127)), epoch << 7);
            __syncwarp();
            mbar_arrive_if(BAR(B_X1), lane == 0);
        } else if (warp == 9) {
            _Pragma("unroll 1") for (int v = 0; v < 9; v++) {
                const int c = (v * 11) >> 5, m = v - 3 * c;
                validate(v, 0, G2A + ((c & 1) ? (m ? m - 1 : 4) : m ? m + 1 : 5) * 16384, offsetof(Scratch, hh) + (tile * 24 + (kh * 4 + m + (m >= dq)) * 3 + (c ^ (c < 2))) * 16384);
            }
        } else if (elect()) {
            asm volatile("cp.async.bulk.wait_group 0;" ::: "memory");
            fence_async_glob();
            signal_cnt((uint32_t*)paddv(P.scr, C_ZO * 128 + (lds32(sb + HT) & 127)), 1);
            {
                int g = 0, c = 0, m = -3;
                _Pragma("unroll 1") for (int n = 0; n < 12; n++) {
                    const uint32_t st = sb + g2b_at(g) + rank * 10240, f = BAR(B_G2F + g);
                    mbar_wait_cluster(BAR(B_G2E + g), n >= 6);
                    mbar_expect(f, 20480);
                    if (m < 0) tma3d_mc(st, &M.wn, (js * 3 + n) * 64 + rank * 32, dq * 5, f);
                    else tma5d_mc(st, &M.wd, ((kh * 4 + m + (m >= dq)) * 3 + (c ^ (c < 2))) * 8 + rank * 4, dq * 5, f);
                    g = g == 5 ? 0 : g + 1;
                    if (++m == 3) { m = 0; c++; }
                }
            }
        }
        PROF_EXIT();
    }
}

typedef CUresult (*EncodeFn)(CUtensorMap*, CUtensorMapDataType, cuuint32_t, void*, const cuuint64_t*, const cuuint64_t*, const cuuint32_t*, const cuuint32_t*,
                             CUtensorMapInterleave, CUtensorMapSwizzle, CUtensorMapL2promotion, CUtensorMapFloatOOBfill);
void enc(EncodeFn fn, CUtensorMap* m, const void* ptr, int rank, const cuuint64_t* dims, const cuuint64_t* strides, const cuuint32_t* box, CUtensorMapSwizzle sw,
         CUtensorMapL2promotion pr = CU_TENSOR_MAP_L2_PROMOTION_L2_128B) {
    cuuint32_t es[5] = {1, 1, 1, 1, 1};
    fn(m, CU_TENSOR_MAP_DATA_TYPE_BFLOAT16, rank, (void*)ptr, dims, strides, box, es, CU_TENSOR_MAP_INTERLEAVE_NONE, sw, pr, CU_TENSOR_MAP_FLOAT_OOB_FILL_NONE);
}
#define LD(kind, r, t) (((t) << 8) | ((kind) << 4) | (r))
Sched h_sched = {{LD(1,0,800), LD(0,1,1220), LD(0,2,2060), LD(1,1,2900), LD(1,2,3320), LD(2,0,3740), LD(2,1,4160), LD(2,2,4580), LD(2,3,5000), LD(2,4,5420), LD(1,3,5840), LD(0,3,6260), LD(0,4,7100), LD(1,4,7940)},
                 {0x61, 0x632, 0x4, 0x5, 0x0}, 1000, 2, 3, 5517840, 1455168, 600, 150};
#define PROMO CU_TENSOR_MAP_L2_PROMOTION_L2_128B
}

extern "C" void kernel_launch(void* const* d_in, const int* in_sizes, int n_in, void* d_out, int out_size) {
    void* fnp = nullptr; cudaDriverEntryPointQueryResult st;
    cudaGetDriverEntryPoint("cuTensorMapEncodeTiled", &fnp, cudaEnableDefault, &st);
    EncodeFn fn = (EncodeFn)fnp;
    void* scr;
    cudaGetSymbolAddress(&scr, g_s);
    Maps M; Ptrs P;
    P.k = (const char*)d_in[1]; P.v = (const char*)d_in[2]; P.shift = (const char*)d_in[3];
    P.ssm = (const char*)d_in[4]; P.ssmD = (const char*)d_in[5]; P.Wg = (const char*)d_in[7]; P.Wu = (const char*)d_in[8];
    P.Wd = (const char*)d_in[9]; P.c = (const char*)d_in[10]; P.scr = (char*)scr; P.s = h_sched;
    { cuuint64_t d[3] = {640, 256, 8}, s[2] = {8 * 1280, 1280}; cuuint32_t b1[3] = {32, 9, 8}, b2[3] = {32, 8, 8};
      enc(fn, &M.k, P.k, 3, d, s, b1, CU_TENSOR_MAP_SWIZZLE_64B, PROMO); enc(fn, &M.v, P.v, 3, d, s, b2, CU_TENSOR_MAP_SWIZZLE_64B, PROMO); }
    { cuuint64_t d[4] = {640, 2, 256, 4}, s[3] = {1280, 8 * 1280, 2 * 1280}; cuuint32_t b1[4] = {32, 2, 8, 4};
      enc(fn, &M.q, d_in[0], 4, d, s, b1, CU_TENSOR_MAP_SWIZZLE_64B, PROMO); enc(fn, &M.o1, d_out, 4, d, s, b1, CU_TENSOR_MAP_SWIZZLE_64B, PROMO); }
    { cuuint64_t d[3] = {64, 640, 24}, s[2] = {3072, 128}; cuuint32_t bx[2][3] = {{64, 32, 2}, {64, 64, 1}};
      for (int i = 0; i < 4; i++) enc(fn, &M.w[i], (i & 1) ? P.Wu : P.Wg, 3, d, s, bx[i >> 1], CU_TENSOR_MAP_SWIZZLE_128B); }
    { cuuint64_t d[5] = {32, 2, 192, 4, 20}, s[4] = {1280, 8 * 1280, 2 * 1280, 64}; cuuint32_t b1[5] = {32, 2, 4, 4, 5};
      enc(fn, &M.wd, P.Wd, 5, d, s, b1, CU_TENSOR_MAP_SWIZZLE_64B); }
    { cuuint64_t d[3] = {32, 1536, 20}, s[2] = {1280, 64}; cuuint32_t b1[3] = {32, 32, 5};
      enc(fn, &M.wn, P.Wd, 3, d, s, b1, CU_TENSOR_MAP_SWIZZLE_64B); }
    { cuuint64_t d[2] = {3840, 640}, s[1] = {7680}; cuuint32_t b1[2] = {64, 160};
      enc(fn, &M.wm, d_in[11], 2, d, s, b1, CU_TENSOR_MAP_SWIZZLE_128B); }
    { cuuint64_t d[2] = {640, 2048}, s[1] = {1280}; cuuint32_t b1[2] = {80, 16};
      enc(fn, &M.out, d_out, 2, d, s, b1, CU_TENSOR_MAP_SWIZZLE_NONE); }
    cudaFuncSetAttribute(fused_kernel, cudaFuncAttributeMaxDynamicSharedMemorySize, SMEM_BYTES);
    fused_kernel<<<132, 384, SMEM_BYTES>>>(P, M);
}
```

```cpp
#include <cuda_runtime.h>
#include <cuda_bf16.h>
#include <cuda.h>
#include <stdint.h>
#include <stddef.h>
#include <type_traits>

namespace {

constexpr int S_ = 2048, D_ = 640;

struct Scratch {
    uint32_t cnt[8 * 2048];
    uint4 kvT[D_ * 256];
    uint4 yB[D_ * 256];
    uint4 z[D_ * 256];
    uint4 hh[16 * 24 * 1024];
    uint2 st1[128 * 64], st2[128 * 64];
    uint32_t mod[3840];
    uint2 ut[5 * 3072];
};
__device__ __align__(8192) Scratch g_s;
#define SC(f, off) padd(P.scr, (uint32_t)offsetof(Scratch, f) + (off))
constexpr int C_KV = 0  , C_ZO = 31, C_Y = 64, C_Z = 128  , C_HH = 448  ;
#define GSTAMPIF(c, i) do {} while (0)
#define STAMPIF(c, i) do {} while (0)
#define STAMPL(c, i) do {} while (0)
#define PROF_EXIT() do {} while (0)
#define KSTAMP(c, i) do {} while (0)
#define STAMP(i) do {} while (0)

constexpr uint32_t WR = 163840, MISC = 229376, SMEM_BYTES = 232448;
constexpr uint32_t XP = 4112, KVP = 8704, PP = 4352;
constexpr uint32_t PB = 65536, XB = PB + 4 * PP;
constexpr uint32_t UST = 98304;
constexpr uint32_t KV3 = WR + 32768, SHT = KV3 + 2 * KVP;
constexpr uint32_t DS = SHT + 5120, H4 = DS + 1280, HO0 = H4 + XP + 48, HO1 = 4 * XP + 32;
__host__ __device__ constexpr uint32_t h_at(int r) { return r == 4 ? H4 : r * XP; }
static_assert(HO0 % 128 == 64 && H4 % 128 == 0 && HO1 % 128 == 96 && HO0 + XP <= MISC, "bank offsets");
constexpr uint32_t QS = 131072, YS = QS + 20480;
__host__ __device__ constexpr uint32_t kv_at(int r) { return r * KVP + (r >= 3 ? KV3 - 3 * KVP : UST); }
__host__ __device__ constexpr uint32_t x_at(int r) { return XB - (r & 1) * 32768 + (r >> 1) * XP; }
constexpr uint32_t BARS = MISC, HT = MISC + 680, TAB1 = MISC + 688, TAB2 = TAB1 + 32 * 48;
constexpr uint32_t CT = TAB1, RAW = TAB1 + 256, MR = TAB1 + 768, CS_TAB = TAB1 + 1024, PS = TAB1 + 1632, PRE = PS + 512;
constexpr uint32_t GBT = TAB1 + 64, G2B = 8192, G2A = 131072;
__host__ __device__ constexpr uint32_t g2b_at(int g) { return G2B + (g < 4 ? g + 2 : g - 4) * 20480; }
__host__ __device__ constexpr uint32_t w2_at(int it) { return it < 4 ? WR + it * 16384 : (it & 1) ? (it >> 1) * 16384 - 32768 : WR + (it >> 1) * 16384 - 32768; }
__host__ __device__ constexpr int w2_bar(int it);
enum { B_KV = 0, B_H = 5, B_Q = 10, B_XF = 15, B_YF = 20, B_AF = 25, B_WF = 35, B_G2F = 39, B_CR = 45, B_RT = 46, B_WE = 47, B_G2E = 51,
       B_S0 = 57, B_HD = 58, B_UD = 60, B_T1 = 61, B_FF = 62  , B_GO = 65, B_UF = 66, B_X1 = 67, B_FD = 68, B_WX = 73  , B_HE = 76  , NBARS = 79, B_IN = NBARS };
__host__ __device__ constexpr uint32_t bar_count(int i) {
    return (i > B_XF && i < B_YF) ? 5 : ((i >= B_YF && i < B_AF) || (i >= B_G2F && i < B_CR)) ? 2 : i < B_WE ? 1 : i < B_S0 ? 16 : i < B_UD ? 8 : i == B_UD ? 9 : i == B_T1 ? 3 : i == B_X1 ? 1 : i == B_FF ? 6 : i == B_FF + 1 ? 4 : (i == B_GO || i == B_FF + 2) ? 8 : i < B_WX ? 2 : i < B_HE ? 1 : 8;
}
__host__ __device__ constexpr int w2_bar(int it) { return it < 4 ? B_WF + it : ((it & 1) ? B_WX : B_WF) + (it >> 1) - 2; }
#define SG 5
#define RD4 0
#define ESPLIT 1
#define PW 0
#define EARLY(x)
#define LATE(x) x
#define HPS 0xca864310u
#define B2S 0xa88765
#define KB_UT 4
#define NPF 64
#define FA 24
#define MAP 2
#define FMAP 1
constexpr int NLD = 28;
struct Sched { uint32_t ld[NLD], wl[5], d_sp, spin, g_sp, xd; };

__device__ __forceinline__ uint32_t smem_u32(const void* p) { return (uint32_t)__cvta_generic_to_shared(p); }
__device__ __forceinline__ void mbar_init(uint32_t bar, uint32_t cnt) { asm volatile("mbarrier.init.shared::cta.b64 [%0], %1;" :: "r"(bar), "r"(cnt) : "memory"); }
__device__ __forceinline__ void mbar_expect(uint32_t bar, uint32_t bytes) { asm volatile("mbarrier.arrive.expect_tx.shared::cta.b64 _, [%0], %1;" :: "r"(bar), "r"(bytes) : "memory"); }
__device__ __forceinline__ void mbar_arrive(uint32_t bar) { asm volatile("mbarrier.arrive.shared::cta.b64 _, [%0];" :: "r"(bar) : "memory"); }
__device__ __forceinline__ void mbar_arrive_if(uint32_t bar, bool p) { asm volatile("{ .reg .pred p; setp.ne.b32 p, %1, 0; @p mbarrier.arrive.shared::cta.b64 _, [%0]; }" :: "r"(bar), "r"((int)p) : "memory"); }
__device__ __forceinline__ void mbar_arrive_remote_if(uint32_t bar, bool p) { asm volatile("{ .reg .pred p; setp.ne.b32 p, %1, 0; @p mbarrier.arrive.shared::cluster.b64 _, [%0]; }" :: "r"(bar), "r"((int)p) : "memory"); }
__device__ __forceinline__ void mbar_wait(uint32_t bar, uint32_t parity) {
    asm volatile("{\n .reg .pred p, q; .reg .u32 c; mov.u32 c, 0;\n LAB_WAIT:\n mbarrier.try_wait.parity.shared::cta.b64 p, [%0], %1;\n"
                 " add.u32 c, c, 1; setp.lt.and.u32 q, c, 16384, !p;\n @q bra LAB_WAIT;\n }" :: "r"(bar), "r"(parity) : "memory");
}
__device__ __forceinline__ bool mbar_test(uint32_t bar, uint32_t parity) {
    uint32_t ok; asm volatile("{ .reg .pred p; mbarrier.test_wait.parity.shared::cta.b64 p, [%1], %2; selp.u32 %0, 1, 0, p; }" : "=r"(ok) : "r"(bar), "r"(parity) : "memory"); return ok;
}
__device__ __forceinline__ void wait_clock(uint32_t t0, uint32_t d) {
    asm volatile("{\n .reg .pred p; .reg .u32 t;\n LAB_CLK:\n mov.u32 t, %%clock; sub.u32 t, t, %0; setp.lt.u32 p, t, %1;\n @p bra LAB_CLK;\n }" :: "r"(t0), "r"(d) : "memory");
}
__device__ __forceinline__ void pause(uint32_t d) { uint32_t t; asm volatile("mov.u32 %0, %%clock;" : "=r"(t)); wait_clock(t, d); }
__device__ __forceinline__ void mbar_wait_cluster(uint32_t bar, uint32_t parity) {
    asm volatile("{\n .reg .pred p, q; .reg .u32 c; mov.u32 c, 0;\n LAB_WAIT:\n mbarrier.try_wait.parity.acquire.cluster.shared::cta.b64 p, [%0], %1;\n"
                 " add.u32 c, c, 1; setp.lt.and.u32 q, c, 16384, !p;\n @q bra LAB_WAIT;\n }" :: "r"(bar), "r"(parity) : "memory");
}
__device__ __forceinline__ bool elect() { uint32_t p; asm volatile("{ .reg .pred p; elect.sync _|p, 0xffffffff; selp.u32 %0, 1, 0, p; }" : "=r"(p)); return p; }
__device__ __forceinline__ void pf_map(const CUtensorMap* m) { asm volatile("prefetch.tensormap [%0];" :: "l"(m) : "memory"); }
__device__ __forceinline__ void bar_sync(int id, int n) { asm volatile("bar.sync %0, %1;" :: "r"(id), "r"(n) : "memory"); }
__device__ __forceinline__ void bar_arrive(int id, int n) { asm volatile("bar.arrive %0, %1;" :: "r"(id), "r"(n) : "memory"); }
__device__ __forceinline__ void fence_async_smem() { asm volatile("fence.proxy.async.shared::cta;" ::: "memory"); }
__device__ __forceinline__ void fence_async_glob() { asm volatile("fence.proxy.async.global;" ::: "memory"); }
__device__ __forceinline__ void bulk_g2s(uint32_t dst, const void* src, uint32_t bytes, uint32_t bar) {
    asm volatile("cp.async.bulk.shared::cluster.global.mbarrier::complete_tx::bytes [%0], [%1], %2, [%3];" :: "r"(dst), "l"(src), "r"(bytes), "r"(bar) : "memory");
}
__device__ __forceinline__ void pf_l2(const void* src, uint32_t bytes) { asm volatile("cp.async.bulk.prefetch.L2.global [%0], %1;" :: "l"(src), "r"(bytes) : "memory"); }
__device__ __forceinline__ void tma2d(uint32_t dst, const CUtensorMap* m, int c0, int c1, uint32_t bar) {
    asm volatile("cp.async.bulk.tensor.2d.shared::cluster.global.mbarrier::complete_tx::bytes [%0], [%1, {%3, %4}], [%2];" :: "r"(dst), "l"(m), "r"(bar), "r"(c0), "r"(c1) : "memory");
}
__device__ __forceinline__ void tma3d(uint32_t dst, const CUtensorMap* m, int c0, int c1, int c2, uint32_t bar) {
    asm volatile("cp.async.bulk.tensor.3d.shared::cluster.global.mbarrier::complete_tx::bytes [%0], [%1, {%3, %4, %5}], [%2];" :: "r"(dst), "l"(m), "r"(bar), "r"(c0), "r"(c1), "r"(c2) : "memory");
}
__device__ __forceinline__ void tma4d(uint32_t dst, const CUtensorMap* m, int c0, int c2, uint32_t bar) {
    asm volatile("cp.async.bulk.tensor.4d.shared::cluster.global.mbarrier::complete_tx::bytes [%0], [%1, {%3, %5, %4, %5}], [%2];" :: "r"(dst), "l"(m), "r"(bar), "r"(c0), "r"(c2), "r"(0) : "memory");
}
__device__ __forceinline__ void tma4d_st(const CUtensorMap* m, uint32_t src, int c0, int c2) {
    asm volatile("cp.async.bulk.tensor.4d.global.shared::cta.bulk_group [%0, {%2, %4, %3, %4}], [%1];" :: "l"(m), "r"(src), "r"(c0), "r"(c2), "r"(0) : "memory");
}
__device__ __forceinline__ void tma5d_mc(uint32_t dst, const CUtensorMap* m, int c2, int c4, uint32_t bar) {
    asm volatile("cp.async.bulk.tensor.5d.shared::cluster.global.mbarrier::complete_tx::bytes.multicast::cluster [%0], [%1, {%5, %5, %3, %5, %4}], [%2], %6;"
                 :: "r"(dst), "l"(m), "r"(bar), "r"(c2), "r"(c4), "r"(0), "h"((uint16_t)3) : "memory");
}
__device__ __forceinline__ void tma3d_mc(uint32_t dst, const CUtensorMap* m, int c1, int c2, uint32_t bar, uint16_t mask = 3) {
    asm volatile("cp.async.bulk.tensor.3d.shared::cluster.global.mbarrier::complete_tx::bytes.multicast::cluster [%0], [%1, {%5, %3, %4}], [%2], %6;"
                 :: "r"(dst), "l"(m), "r"(bar), "r"(c1), "r"(c2), "r"(0), "h"(mask) : "memory");
}
__device__ __forceinline__ void tma2d_red(const CUtensorMap* m, uint32_t src, int c0, int c1) {
    asm volatile("cp.reduce.async.bulk.tensor.2d.global.shared::cta.add.bulk_group [%0, {%2, %3}], [%1];" :: "l"(m), "r"(src), "r"(c0), "r"(c1) : "memory");
}
#define FENCE_REL "fence.release.gpu;"
__device__ __forceinline__ void signal_cnt(uint32_t* c, uint32_t inc) {
    asm volatile(FENCE_REL "\n fence.proxy.async.global;\n red.relaxed.gpu.global.add.u32 [%0], %1; red.relaxed.gpu.global.add.u32 [%0+4096], %1;" :: "l"(c), "r"(inc) : "memory");
}
template<int INC = 4> __device__ __forceinline__ void hint_cnt(void* c, bool p) { asm volatile("{ .reg .pred p; setp.ne.b32 p, %1, 0; @p red.relaxed.gpu.global.add.u32 [%0], %2; }" :: "l"(c), "r"((int)p), "n"(INC) : "memory"); }
__device__ __forceinline__ void pre_add(uint32_t a, bool p) { asm volatile("{ .reg .pred p; setp.ne.b32 p, %1, 0; @p red.shared.add.u32 [%0], 1; }" :: "r"(a), "r"((int)p) : "memory"); }
__device__ __forceinline__ uint32_t tagbit(uint32_t x, uint32_t tag) { uint32_t r; asm("lop3.b32 %0, %1, %2, 1, 0xd8;" : "=r"(r) : "r"(x), "r"(tag)); return r; }
__device__ __forceinline__ void stg_v4(void* p, uint32_t x, uint32_t y, uint32_t z, uint32_t w) { asm volatile("st.relaxed.gpu.global.v4.b32 [%0], {%1,%2,%3,%4};" :: "l"(p), "r"(x), "r"(y), "r"(z), "r"(w) : "memory"); }
template<int OFF> __device__ __forceinline__ void stg_tag2(char* p, uint32_t x, uint32_t y, uint32_t z, uint32_t w, uint32_t x2, uint32_t y2, uint32_t z2, uint32_t w2, uint32_t tag) {
    stg_v4(p, tagbit(x, tag), y, z, w); stg_v4(p + OFF, tagbit(x2, tag), y2, z2, w2);
}
__device__ __forceinline__ void wait_dual(const uint32_t* c, uint32_t slot, uint32_t d, uint32_t target, uint32_t bar, uint32_t par) {
    asm volatile("{\n .reg .pred p, q, t; .reg .u32 n, v, w; mov.u32 n, 0;\n LAB_PD:\n ld.volatile.shared.u32 v, [%2]; ld.volatile.shared.u32 w, [%2+16];\n"
                 " mbarrier.test_wait.parity.shared::cta.b64 t, [%4], %5;\n"
                 " sub.u32 v, v, %3; sub.u32 w, w, %3; and.b32 v, v, w; setp.ge.and.s32 p, v, 0, t;\n @p bra LAB_PDD;\n"
                 " and.b32 w, n, 1; setp.eq.u32 q, w, 0; @q cp.async.cg.shared.global [%1], [%0], 16; @q cp.async.cg.shared.global [%1+16], [%0+4096], 16;\n"
                 " add.u32 n, n, 1; setp.lt.u32 q, n, 200000;\n @q bra LAB_PD;\n LAB_PDD:\n }" :: "l"(c), "r"(slot), "r"(slot + d), "r"(target), "r"(bar), "r"(par) : "memory");
}
__device__ __forceinline__ void poll_cnt(const uint32_t* c, uint32_t target) {
    asm volatile("{\n .reg .pred p, q; .reg .u32 c, v; mov.u32 c, 0;\n LAB_POLL:\n ld.relaxed.gpu.global.u32 v, [%0];\n sub.u32 v, v, %1; setp.ge.s32 p, v, 0;\n @p bra LAB_PDONE;\n"
                 " add.u32 c, c, 1; setp.lt.u32 q, c, 20000;\n @q bra LAB_POLL;\n LAB_PDONE:\n fence.acquire.gpu;\n }" :: "l"(c), "r"(target) : "memory");
}
template<int N1, int S1, int N2, int S2> __device__ __forceinline__ void ll_read2(const char* p, uint32_t tag, float2* out) {
    constexpr int N = N1 * N2;
    _Pragma("unroll 1") for (int it = 0; it < 20000; it++) {
        uint32_t bad = 0;
        #pragma unroll
        for (int i = 0; i < N; i++) asm volatile("ld.relaxed.gpu.global.v2.f32 {%0, %1}, [%2];" : "=f"(out[i].x), "=f"(out[i].y) : "l"(p + (i / N2) * S1 + (i % N2) * S2) : "memory");
        #pragma unroll
        for (int i = 0; i < N; i++) bad |= (__float_as_uint(out[i].x) ^ tag) | (__float_as_uint(out[i].y) ^ tag);
        if (!__any_sync(~0u, (bad & 7) != 0)) break;
        asm volatile("nanosleep.u32 200;");
    }
}
__device__ __forceinline__ void ll_write1(void* p, float a, uint32_t tag) {
    asm volatile("{ .reg .b64 x; mov.b64 x, {%1, %2}; st.relaxed.gpu.global.b64 [%0], x; }" :: "l"(p), "r"(__float_as_uint(a)), "r"(tag) : "memory");
}
__device__ __forceinline__ uint4 lds128(uint32_t a) { uint4 v; asm volatile("ld.shared.v4.b32 {%0,%1,%2,%3}, [%4];" : "=r"(v.x), "=r"(v.y), "=r"(v.z), "=r"(v.w) : "r"(a) : "memory"); return v; }
__device__ __forceinline__ void sts128(uint32_t a, uint32_t x, uint32_t y, uint32_t z, uint32_t w) { asm volatile("st.shared.v4.b32 [%0], {%1,%2,%3,%4};" :: "r"(a), "r"(x), "r"(y), "r"(z), "r"(w) : "memory"); }
__device__ __forceinline__ void sts32(uint32_t a, uint32_t x) { asm volatile("st.shared.b32 [%0], %1;" :: "r"(a), "r"(x) : "memory"); }
__device__ __forceinline__ uint4 ldg_rlx128(const void* p) { uint4 v; asm volatile("{ .reg .b64 x, y; ld.relaxed.gpu.global.v2.b64 {x, y}, [%4]; mov.b64 {%0, %1}, x; mov.b64 {%2, %3}, y; }" : "=r"(v.x), "=r"(v.y), "=r"(v.z), "=r"(v.w) : "l"(p) : "memory"); return v; }
__device__ __forceinline__ uint32_t lds32(uint32_t a) { uint32_t v; asm volatile("ld.shared.b32 %0, [%1];" : "=r"(v) : "r"(a) : "memory"); return v; }
__device__ __forceinline__ void stg128(void* p, uint32_t x, uint32_t y, uint32_t z, uint32_t w) { asm volatile("st.global.v4.b32 [%0], {%1,%2,%3,%4};" :: "l"(p), "r"(x), "r"(y), "r"(z), "r"(w) : "memory"); }
__device__ __forceinline__ char* padd(const void* p, uint32_t off) { char* r; asm("{ .reg .u64 t; cvt.u64.u32 t, %2; add.u64 %0, %1, t; }" : "=l"(r) : "l"(p), "r"(off)); return r; }
__device__ __forceinline__ char* paddv(const void* p, uint32_t off) { char* r; asm volatile("{ .reg .u64 t; cvt.u64.u32 t, %2; add.u64 %0, %1, t; }" : "=l"(r) : "l"(p), "r"(off)); return r; }
__device__ __forceinline__ uint32_t prmt(uint32_t a, uint32_t b, uint32_t s) { uint32_t r; asm("prmt.b32 %0, %1, %2, %3;" : "=r"(r) : "r"(a), "r"(b), "r"(s)); return r; }
__device__ __forceinline__ uint32_t pack2(float lo, float hi) { uint32_t r; asm("cvt.rn.bf16x2.f32 %0, %1, %2;" : "=r"(r) : "f"(hi), "f"(lo)); return r; }
__device__ __forceinline__ uint32_t pack2relu(float lo, float hi) { uint32_t r; asm("cvt.rn.relu.bf16x2.f32 %0, %1, %2;" : "=r"(r) : "f"(hi), "f"(lo)); return r; }
__device__ __forceinline__ float bflo(uint32_t w) { return __uint_as_float(w << 16); }
__device__ __forceinline__ float bfhi(uint32_t w) { return __uint_as_float(w & 0xffff0000u); }
__device__ __forceinline__ float bfround(float x) { return bflo(pack2(x, x)); }
__device__ __forceinline__ uint32_t hmul2(uint32_t a, uint32_t b) { uint32_t r; asm("mul.rn.bf16x2 %0, %1, %2;" : "=r"(r) : "r"(a), "r"(b)); return r; }
__device__ __forceinline__ uint32_t hadd2(uint32_t a, uint32_t b) { uint32_t r; asm("add.rn.bf16x2 %0, %1, %2;" : "=r"(r) : "r"(a), "r"(b)); return r; }
__device__ __forceinline__ uint32_t hsub2(uint32_t a, uint32_t b) { uint32_t r; asm("sub.rn.bf16x2 %0, %1, %2;" : "=r"(r) : "r"(a), "r"(b)); return r; }
__device__ __forceinline__ uint32_t hfma2(uint32_t a, uint32_t b, uint32_t c) { uint32_t r; asm("fma.rn.bf16x2 %0, %1, %2, %3;" : "=r"(r) : "r"(a), "r"(b), "r"(c)); return r; }
__device__ __forceinline__ void wg_fence() { asm volatile("wgmma.fence.sync.aligned;" ::: "memory"); }
__device__ __forceinline__ void wg_commit() { asm volatile("wgmma.commit_group.sync.aligned;" ::: "memory"); }
template<int N> __device__ __forceinline__ void wg_wait() { asm volatile("wgmma.wait_group.sync.aligned %0;" :: "n"(N) : "memory"); }
template<int N> __device__ __forceinline__ void pin(float* d) {
    #pragma unroll
    for (int i = 0; i < N; i++) asm volatile("" : "+f"(d[i]) :: "memory");
}
__device__ __forceinline__ uint32_t dlo(uint32_t addr, uint32_t lbo) { return ((addr & 0x3FFFF) >> 4) | ((lbo >> 4) << 16); }
__host__ __device__ constexpr uint32_t dhi(uint32_t sbo, uint32_t sw) { return (sbo >> 4) | (sw << 30); }

template<int N> struct WG;
template<> struct WG<8> { template<int TA, int TB> static __device__ __forceinline__ void ss(float* d, uint32_t alo, uint32_t ahi, uint32_t blo, uint32_t bhi, int sd) {
  asm volatile("{ .reg .pred p; .reg .b64 da, db; mov.b64 da, {%4,%5}; mov.b64 db, {%6,%7}; setp.ne.b32 p, %8, 0;\n"
    "wgmma.mma_async.sync.aligned.m64n8k16.f32.bf16.bf16 {%0,%1,%2,%3}, da, db, p, 1, 1, %9, %10; }"
    : "+f"(d[0]),"+f"(d[1]),"+f"(d[2]),"+f"(d[3])
    : "r"(alo), "r"(ahi), "r"(blo), "r"(bhi), "r"(sd), "n"(TA), "n"(TB)); }
};
template<> struct WG<16> { template<int TA, int TB> static __device__ __forceinline__ void ss(float* d, uint32_t alo, uint32_t ahi, uint32_t blo, uint32_t bhi, int sd) {
  asm volatile("{ .reg .pred p; .reg .b64 da, db; mov.b64 da, {%8,%9}; mov.b64 db, {%10,%11}; setp.ne.b32 p, %12, 0;\n"
    "wgmma.mma_async.sync.aligned.m64n16k16.f32.bf16.bf16 {%0,%1,%2,%3,%4,%5,%6,%7}, da, db, p, 1, 1, %13, %14; }"
    : "+f"(d[0]),"+f"(d[1]),"+f"(d[2]),"+f"(d[3]),"+f"(d[4]),"+f"(d[5]),"+f"(d[6]),"+f"(d[7])
    : "r"(alo), "r"(ahi), "r"(blo), "r"(bhi), "r"(sd), "n"(TA), "n"(TB)); }
  template<int TB> static __device__ __forceinline__ void rs(float* d, uint32_t a0, uint32_t a1, uint32_t a2, uint32_t a3, uint32_t blo, uint32_t bhi, int sd) {
  asm volatile("{ .reg .pred p; .reg .b64 db; mov.b64 db, {%12,%13}; setp.ne.b32 p, %15, 0;\n"
    "wgmma.mma_async.sync.aligned.m64n16k16.f32.bf16.bf16 {%0,%1,%2,%3,%4,%5,%6,%7}, {%8,%9,%10,%11}, db, p, 1, 1, %14; }"
    : "+f"(d[0]),"+f"(d[1]),"+f"(d[2]),"+f"(d[3]),"+f"(d[4]),"+f"(d[5]),"+f"(d[6]),"+f"(d[7])
    : "r"(a0), "r"(a1), "r"(a2), "r"(a3), "r"(blo), "r"(bhi), "n"(TB), "r"(sd)); }
};
template<> struct WG<32> { template<int TA, int TB> static __device__ __forceinline__ void ss(float* d, uint32_t alo, uint32_t ahi, uint32_t blo, uint32_t bhi, int sd) {
  asm volatile("{ .reg .pred p; .reg .b64 da, db; mov.b64 da, {%16,%17}; mov.b64 db, {%18,%19}; setp.ne.b32 p, %20, 0;\n"
    "wgmma.mma_async.sync.aligned.m64n32k16.f32.bf16.bf16 {%0,%1,%2,%3,%4,%5,%6,%7,%8,%9,%10,%11,%12,%13,%14,%15}, da, db, p, 1, 1, %21, %22; }"
    : "+f"(d[0]),"+f"(d[1]),"+f"(d[2]),"+f"(d[3]),"+f"(d[4]),"+f"(d[5]),"+f"(d[6]),"+f"(d[7]),"+f"(d[8]),"+f"(d[9]),"+f"(d[10]),"+f"(d[11]),"+f"(d[12]),"+f"(d[13]),"+f"(d[14]),"+f"(d[15])
    : "r"(alo), "r"(ahi), "r"(blo), "r"(bhi), "r"(sd), "n"(TA), "n"(TB)); }
  template<int TB> static __device__ __forceinline__ void rs(float* d, uint32_t a0, uint32_t a1, uint32_t a2, uint32_t a3, uint32_t blo, uint32_t bhi, int sd) {
  asm volatile("{ .reg .pred p; .reg .b64 db; mov.b64 db, {%20,%21}; setp.ne.b32 p, %23, 0;\n"
    "wgmma.mma_async.sync.aligned.m64n32k16.f32.bf16.bf16 {%0,%1,%2,%3,%4,%5,%6,%7,%8,%9,%10,%11,%12,%13,%14,%15}, {%16,%17,%18,%19}, db, p, 1, 1, %22; }"
    : "+f"(d[0]),"+f"(d[1]),"+f"(d[2]),"+f"(d[3]),"+f"(d[4]),"+f"(d[5]),"+f"(d[6]),"+f"(d[7]),"+f"(d[8]),"+f"(d[9]),"+f"(d[10]),"+f"(d[11]),"+f"(d[12]),"+f"(d[13]),"+f"(d[14]),"+f"(d[15])
    : "r"(a0), "r"(a1), "r"(a2), "r"(a3), "r"(blo), "r"(bhi), "n"(TB), "r"(sd)); }
};
template<> struct WG<48> { template<int TA, int TB> static __device__ __forceinline__ void ss(float* d, uint32_t alo, uint32_t ahi, uint32_t blo, uint32_t bhi, int sd) {
  asm volatile("{ .reg .pred p; .reg .b64 da, db; mov.b64 da, {%24,%25}; mov.b64 db, {%26,%27}; setp.ne.b32 p, %28, 0;\n"
    "wgmma.mma_async.sync.aligned.m64n48k16.f32.bf16.bf16 {%0,%1,%2,%3,%4,%5,%6,%7,%8,%9,%10,%11,%12,%13,%14,%15,%16,%17,%18,%19,%20,%21,%22,%23}, da, db, p, 1, 1, %29, %30; }"
    : "+f"(d[0]),"+f"(d[1]),"+f"(d[2]),"+f"(d[3]),"+f"(d[4]),"+f"(d[5]),"+f"(d[6]),"+f"(d[7]),"+f"(d[8]),"+f"(d[9]),"+f"(d[10]),"+f"(d[11]),"+f"(d[12]),"+f"(d[13]),"+f"(d[14]),"+f"(d[15]),"+f"(d[16]),"+f"(d[17]),"+f"(d[18]),"+f"(d[19]),"+f"(d[20]),"+f"(d[21]),"+f"(d[22]),"+f"(d[23])
    : "r"(alo), "r"(ahi), "r"(blo), "r"(bhi), "r"(sd), "n"(TA), "n"(TB)); }
  template<int TB> static __device__ __forceinline__ void rs(float* d, uint32_t a0, uint32_t a1, uint32_t a2, uint32_t a3, uint32_t blo, uint32_t bhi, int sd) {
  asm volatile("{ .reg .pred p; .reg .b64 db; mov.b64 db, {%28,%29}; setp.ne.b32 p, %31, 0;\n"
    "wgmma.mma_async.sync.aligned.m64n48k16.f32.bf16.bf16 {%0,%1,%2,%3,%4,%5,%6,%7,%8,%9,%10,%11,%12,%13,%14,%15,%16,%17,%18,%19,%20,%21,%22,%23}, {%24,%25,%26,%27}, db, p, 1, 1, %30; }"
    : "+f"(d[0]),"+f"(d[1]),"+f"(d[2]),"+f"(d[3]),"+f"(d[4]),"+f"(d[5]),"+f"(d[6]),"+f"(d[7]),"+f"(d[8]),"+f"(d[9]),"+f"(d[10]),"+f"(d[11]),"+f"(d[12]),"+f"(d[13]),"+f"(d[14]),"+f"(d[15]),"+f"(d[16]),"+f"(d[17]),"+f"(d[18]),"+f"(d[19]),"+f"(d[20]),"+f"(d[21]),"+f"(d[22]),"+f"(d[23])
    : "r"(a0), "r"(a1), "r"(a2), "r"(a3), "r"(blo), "r"(bhi), "n"(TB), "r"(sd)); }
};
template<> struct WG<64> { template<int TA, int TB> static __device__ __forceinline__ void ss(float* d, uint32_t alo, uint32_t ahi, uint32_t blo, uint32_t bhi, int sd) {
  asm volatile("{ .reg .pred p; .reg .b64 da, db; mov.b64 da, {%32,%33}; mov.b64 db, {%34,%35}; setp.ne.b32 p, %36, 0;\n"
    "wgmma.mma_async.sync.aligned.m64n64k16.f32.bf16.bf16 {%0,%1,%2,%3,%4,%5,%6,%7,%8,%9,%10,%11,%12,%13,%14,%15,%16,%17,%18,%19,%20,%21,%22,%23,%24,%25,%26,%27,%28,%29,%30,%31}, da, db, p, 1, 1, %37, %38; }"
    : "+f"(d[0]),"+f"(d[1]),"+f"(d[2]),"+f"(d[3]),"+f"(d[4]),"+f"(d[5]),"+f"(d[6]),"+f"(d[7]),"+f"(d[8]),"+f"(d[9]),"+f"(d[10]),"+f"(d[11]),"+f"(d[12]),"+f"(d[13]),"+f"(d[14]),"+f"(d[15]),"+f"(d[16]),"+f"(d[17]),"+f"(d[18]),"+f"(d[19]),"+f"(d[20]),"+f"(d[21]),"+f"(d[22]),"+f"(d[23]),"+f"(d[24]),"+f"(d[25]),"+f"(d[26]),"+f"(d[27]),"+f"(d[28]),"+f"(d[29]),"+f"(d[30]),"+f"(d[31])
    : "r"(alo), "r"(ahi), "r"(blo), "r"(bhi), "r"(sd), "n"(TA), "n"(TB)); }
  template<int TB> static __device__ __forceinline__ void rs(float* d, uint32_t a0, uint32_t a1, uint32_t a2, uint32_t a3, uint32_t blo, uint32_t bhi, int sd) {
  asm volatile("{ .reg .pred p; .reg .b64 db; mov.b64 db, {%36,%37}; setp.ne.b32 p, %39, 0;\n"
    "wgmma.mma_async.sync.aligned.m64n64k16.f32.bf16.bf16 {%0,%1,%2,%3,%4,%5,%6,%7,%8,%9,%10,%11,%12,%13,%14,%15,%16,%17,%18,%19,%20,%21,%22,%23,%24,%25,%26,%27,%28,%29,%30,%31}, {%32,%33,%34,%35}, db, p, 1, 1, %38; }"
    : "+f"(d[0]),"+f"(d[1]),"+f"(d[2]),"+f"(d[3]),"+f"(d[4]),"+f"(d[5]),"+f"(d[6]),"+f"(d[7]),"+f"(d[8]),"+f"(d[9]),"+f"(d[10]),"+f"(d[11]),"+f"(d[12]),"+f"(d[13]),"+f"(d[14]),"+f"(d[15]),"+f"(d[16]),"+f"(d[17]),"+f"(d[18]),"+f"(d[19]),"+f"(d[20]),"+f"(d[21]),"+f"(d[22]),"+f"(d[23]),"+f"(d[24]),"+f"(d[25]),"+f"(d[26]),"+f"(d[27]),"+f"(d[28]),"+f"(d[29]),"+f"(d[30]),"+f"(d[31])
    : "r"(a0), "r"(a1), "r"(a2), "r"(a3), "r"(blo), "r"(bhi), "n"(TB), "r"(sd)); }
};
template<> struct WG<80> { template<int TA, int TB> static __device__ __forceinline__ void ss(float* d, uint32_t alo, uint32_t ahi, uint32_t blo, uint32_t bhi, int sd) {
  asm volatile("{ .reg .pred p; .reg .b64 da, db; mov.b64 da, {%40,%41}; mov.b64 db, {%42,%43}; setp.ne.b32 p, %44, 0;\n"
    "wgmma.mma_async.sync.aligned.m64n80k16.f32.bf16.bf16 {%0,%1,%2,%3,%4,%5,%6,%7,%8,%9,%10,%11,%12,%13,%14,%15,%16,%17,%18,%19,%20,%21,%22,%23,%24,%25,%26,%27,%28,%29,%30,%31,%32,%33,%34,%35,%36,%37,%38,%39}, da, db, p, 1, 1, %45, %46; }"
    : "+f"(d[0]),"+f"(d[1]),"+f"(d[2]),"+f"(d[3]),"+f"(d[4]),"+f"(d[5]),"+f"(d[6]),"+f"(d[7]),"+f"(d[8]),"+f"(d[9]),"+f"(d[10]),"+f"(d[11]),"+f"(d[12]),"+f"(d[13]),"+f"(d[14]),"+f"(d[15]),"+f"(d[16]),"+f"(d[17]),"+f"(d[18]),"+f"(d[19]),"+f"(d[20]),"+f"(d[21]),"+f"(d[22]),"+f"(d[23]),"+f"(d[24]),"+f"(d[25]),"+f"(d[26]),"+f"(d[27]),"+f"(d[28]),"+f"(d[29]),"+f"(d[30]),"+f"(d[31]),"+f"(d[32]),"+f"(d[33]),"+f"(d[34]),"+f"(d[35]),"+f"(d[36]),"+f"(d[37]),"+f"(d[38]),"+f"(d[39])
    : "r"(alo), "r"(ahi), "r"(blo), "r"(bhi), "r"(sd), "n"(TA), "n"(TB)); }
  template<int TB> static __device__ __forceinline__ void rs(float* d, uint32_t a0, uint32_t a1, uint32_t a2, uint32_t a3, uint32_t blo, uint32_t bhi, int sd) {
  asm volatile("{ .reg .pred p; .reg .b64 db; mov.b64 db, {%44,%45}; setp.ne.b32 p, %47, 0;\n"
    "wgmma.mma_async.sync.aligned.m64n80k16.f32.bf16.bf16 {%0,%1,%2,%3,%4,%5,%6,%7,%8,%9,%10,%11,%12,%13,%14,%15,%16,%17,%18,%19,%20,%21,%22,%23,%24,%25,%26,%27,%28,%29,%30,%31,%32,%33,%34,%35,%36,%37,%38,%39}, {%40,%41,%42,%43}, db, p, 1, 1, %46; }"
    : "+f"(d[0]),"+f"(d[1]),"+f"(d[2]),"+f"(d[3]),"+f"(d[4]),"+f"(d[5]),"+f"(d[6]),"+f"(d[7]),"+f"(d[8]),"+f"(d[9]),"+f"(d[10]),"+f"(d[11]),"+f"(d[12]),"+f"(d[13]),"+f"(d[14]),"+f"(d[15]),"+f"(d[16]),"+f"(d[17]),"+f"(d[18]),"+f"(d[19]),"+f"(d[20]),"+f"(d[21]),"+f"(d[22]),"+f"(d[23]),"+f"(d[24]),"+f"(d[25]),"+f"(d[26]),"+f"(d[27]),"+f"(d[28]),"+f"(d[29]),"+f"(d[30]),"+f"(d[31]),"+f"(d[32]),"+f"(d[33]),"+f"(d[34]),"+f"(d[35]),"+f"(d[36]),"+f"(d[37]),"+f"(d[38]),"+f"(d[39])
    : "r"(a0), "r"(a1), "r"(a2), "r"(a3), "r"(blo), "r"(bhi), "n"(TB), "r"(sd)); }
};
template<> struct WG<96> { template<int TA, int TB> static __device__ __forceinline__ void ss(float* d, uint32_t alo, uint32_t ahi, uint32_t blo, uint32_t bhi, int sd) {
  asm volatile("{ .reg .pred p; .reg .b64 da, db; mov.b64 da, {%48,%49}; mov.b64 db, {%50,%51}; setp.ne.b32 p, %52, 0;\n"
    "wgmma.mma_async.sync.aligned.m64n96k16.f32.bf16.bf16 {%0,%1,%2,%3,%4,%5,%6,%7,%8,%9,%10,%11,%12,%13,%14,%15,%16,%17,%18,%19,%20,%21,%22,%23,%24,%25,%26,%27,%28,%29,%30,%31,%32,%33,%34,%35,%36,%37,%38,%39,%40,%41,%42,%43,%44,%45,%46,%47}, da, db, p, 1, 1, %53, %54; }"
    : "+f"(d[0]),"+f"(d[1]),"+f"(d[2]),"+f"(d[3]),"+f"(d[4]),"+f"(d[5]),"+f"(d[6]),"+f"(d[7]),"+f"(d[8]),"+f"(d[9]),"+f"(d[10]),"+f"(d[11]),"+f"(d[12]),"+f"(d[13]),"+f"(d[14]),"+f"(d[15]),"+f"(d[16]),"+f"(d[17]),"+f"(d[18]),"+f"(d[19]),"+f"(d[20]),"+f"(d[21]),"+f"(d[22]),"+f"(d[23]),"+f"(d[24]),"+f"(d[25]),"+f"(d[26]),"+f"(d[27]),"+f"(d[28]),"+f"(d[29]),"+f"(d[30]),"+f"(d[31]),"+f"(d[32]),"+f"(d[33]),"+f"(d[34]),"+f"(d[35]),"+f"(d[36]),"+f"(d[37]),"+f"(d[38]),"+f"(d[39]),"+f"(d[40]),"+f"(d[41]),"+f"(d[42]),"+f"(d[43]),"+f"(d[44]),"+f"(d[45]),"+f"(d[46]),"+f"(d[47])
    : "r"(alo), "r"(ahi), "r"(blo), "r"(bhi), "r"(sd), "n"(TA), "n"(TB)); }
  template<int TB> static __device__ __forceinline__ void rs(float* d, uint32_t a0, uint32_t a1, uint32_t a2, uint32_t a3, uint32_t blo, uint32_t bhi, int sd) {
  asm volatile("{ .reg .pred p; .reg .b64 db; mov.b64 db, {%52,%53}; setp.ne.b32 p, %55, 0;\n"
    "wgmma.mma_async.sync.aligned.m64n96k16.f32.bf16.bf16 {%0,%1,%2,%3,%4,%5,%6,%7,%8,%9,%10,%11,%12,%13,%14,%15,%16,%17,%18,%19,%20,%21,%22,%23,%24,%25,%26,%27,%28,%29,%30,%31,%32,%33,%34,%35,%36,%37,%38,%39,%40,%41,%42,%43,%44,%45,%46,%47}, {%48,%49,%50,%51}, db, p, 1, 1, %54; }"
    : "+f"(d[0]),"+f"(d[1]),"+f"(d[2]),"+f"(d[3]),"+f"(d[4]),"+f"(d[5]),"+f"(d[6]),"+f"(d[7]),"+f"(d[8]),"+f"(d[9]),"+f"(d[10]),"+f"(d[11]),"+f"(d[12]),"+f"(d[13]),"+f"(d[14]),"+f"(d[15]),"+f"(d[16]),"+f"(d[17]),"+f"(d[18]),"+f"(d[19]),"+f"(d[20]),"+f"(d[21]),"+f"(d[22]),"+f"(d[23]),"+f"(d[24]),"+f"(d[25]),"+f"(d[26]),"+f"(d[27]),"+f"(d[28]),"+f"(d[29]),"+f"(d[30]),"+f"(d[31]),"+f"(d[32]),"+f"(d[33]),"+f"(d[34]),"+f"(d[35]),"+f"(d[36]),"+f"(d[37]),"+f"(d[38]),"+f"(d[39]),"+f"(d[40]),"+f"(d[41]),"+f"(d[42]),"+f"(d[43]),"+f"(d[44]),"+f"(d[45]),"+f"(d[46]),"+f"(d[47])
    : "r"(a0), "r"(a1), "r"(a2), "r"(a3), "r"(blo), "r"(bhi), "n"(TB), "r"(sd)); }
};
template<> struct WG<112> { template<int TA, int TB> static __device__ __forceinline__ void ss(float* d, uint32_t alo, uint32_t ahi, uint32_t blo, uint32_t bhi, int sd) {
  asm volatile("{ .reg .pred p; .reg .b64 da, db; mov.b64 da, {%56,%57}; mov.b64 db, {%58,%59}; setp.ne.b32 p, %60, 0;\n"
    "wgmma.mma_async.sync.aligned.m64n112k16.f32.bf16.bf16 {%0,%1,%2,%3,%4,%5,%6,%7,%8,%9,%10,%11,%12,%13,%14,%15,%16,%17,%18,%19,%20,%21,%22,%23,%24,%25,%26,%27,%28,%29,%30,%31,%32,%33,%34,%35,%36,%37,%38,%39,%40,%41,%42,%43,%44,%45,%46,%47,%48,%49,%50,%51,%52,%53,%54,%55}, da, db, p, 1, 1, %61, %62; }"
    : "+f"(d[0]),"+f"(d[1]),"+f"(d[2]),"+f"(d[3]),"+f"(d[4]),"+f"(d[5]),"+f"(d[6]),"+f"(d[7]),"+f"(d[8]),"+f"(d[9]),"+f"(d[10]),"+f"(d[11]),"+f"(d[12]),"+f"(d[13]),"+f"(d[14]),"+f"(d[15]),"+f"(d[16]),"+f"(d[17]),"+f"(d[18]),"+f"(d[19]),"+f"(d[20]),"+f"(d[21]),"+f"(d[22]),"+f"(d[23]),"+f"(d[24]),"+f"(d[25]),"+f"(d[26]),"+f"(d[27]),"+f"(d[28]),"+f"(d[29]),"+f"(d[30]),"+f"(d[31]),"+f"(d[32]),"+f"(d[33]),"+f"(d[34]),"+f"(d[35]),"+f"(d[36]),"+f"(d[37]),"+f"(d[38]),"+f"(d[39]),"+f"(d[40]),"+f"(d[41]),"+f"(d[42]),"+f"(d[43]),"+f"(d[44]),"+f"(d[45]),"+f"(d[46]),"+f"(d[47]),"+f"(d[48]),"+f"(d[49]),"+f"(d[50]),"+f"(d[51]),"+f"(d[52]),"+f"(d[53]),"+f"(d[54]),"+f"(d[55])
    : "r"(alo), "r"(ahi), "r"(blo), "r"(bhi), "r"(sd), "n"(TA), "n"(TB)); }
  template<int TB> static __device__ __forceinline__ void rs(float* d, uint32_t a0, uint32_t a1, uint32_t a2, uint32_t a3, uint32_t blo, uint32_t bhi, int sd) {
  asm volatile("{ .reg .pred p; .reg .b64 db; mov.b64 db, {%60,%61}; setp.ne.b32 p, %63, 0;\n"
    "wgmma.mma_async.sync.aligned.m64n112k16.f32.bf16.bf16 {%0,%1,%2,%3,%4,%5,%6,%7,%8,%9,%10,%11,%12,%13,%14,%15,%16,%17,%18,%19,%20,%21,%22,%23,%24,%25,%26,%27,%28,%29,%30,%31,%32,%33,%34,%35,%36,%37,%38,%39,%40,%41,%42,%43,%44,%45,%46,%47,%48,%49,%50,%51,%52,%53,%54,%55}, {%56,%57,%58,%59}, db, p, 1, 1, %62; }"
    : "+f"(d[0]),"+f"(d[1]),"+f"(d[2]),"+f"(d[3]),"+f"(d[4]),"+f"(d[5]),"+f"(d[6]),"+f"(d[7]),"+f"(d[8]),"+f"(d[9]),"+f"(d[10]),"+f"(d[11]),"+f"(d[12]),"+f"(d[13]),"+f"(d[14]),"+f"(d[15]),"+f"(d[16]),"+f"(d[17]),"+f"(d[18]),"+f"(d[19]),"+f"(d[20]),"+f"(d[21]),"+f"(d[22]),"+f"(d[23]),"+f"(d[24]),"+f"(d[25]),"+f"(d[26]),"+f"(d[27]),"+f"(d[28]),"+f"(d[29]),"+f"(d[30]),"+f"(d[31]),"+f"(d[32]),"+f"(d[33]),"+f"(d[34]),"+f"(d[35]),"+f"(d[36]),"+f"(d[37]),"+f"(d[38]),"+f"(d[39]),"+f"(d[40]),"+f"(d[41]),"+f"(d[42]),"+f"(d[43]),"+f"(d[44]),"+f"(d[45]),"+f"(d[46]),"+f"(d[47]),"+f"(d[48]),"+f"(d[49]),"+f"(d[50]),"+f"(d[51]),"+f"(d[52]),"+f"(d[53]),"+f"(d[54]),"+f"(d[55])
    : "r"(a0), "r"(a1), "r"(a2), "r"(a3), "r"(blo), "r"(bhi), "n"(TB), "r"(sd)); }
};
template<> struct WG<128> { template<int TA, int TB> static __device__ __forceinline__ void ss(float* d, uint32_t alo, uint32_t ahi, uint32_t blo, uint32_t bhi, int sd) {
  asm volatile("{ .reg .pred p; .reg .b64 da, db; mov.b64 da, {%64,%65}; mov.b64 db, {%66,%67}; setp.ne.b32 p, %68, 0;\n"
    "wgmma.mma_async.sync.aligned.m64n128k16.f32.bf16.bf16 {%0,%1,%2,%3,%4,%5,%6,%7,%8,%9,%10,%11,%12,%13,%14,%15,%16,%17,%18,%19,%20,%21,%22,%23,%24,%25,%26,%27,%28,%29,%30,%31,%32,%33,%34,%35,%36,%37,%38,%39,%40,%41,%42,%43,%44,%45,%46,%47,%48,%49,%50,%51,%52,%53,%54,%55,%56,%57,%58,%59,%60,%61,%62,%63}, da, db, p, 1, 1, %69, %70; }"
    : "+f"(d[0]),"+f"(d[1]),"+f"(d[2]),"+f"(d[3]),"+f"(d[4]),"+f"(d[5]),"+f"(d[6]),"+f"(d[7]),"+f"(d[8]),"+f"(d[9]),"+f"(d[10]),"+f"(d[11]),"+f"(d[12]),"+f"(d[13]),"+f"(d[14]),"+f"(d[15]),"+f"(d[16]),"+f"(d[17]),"+f"(d[18]),"+f"(d[19]),"+f"(d[20]),"+f"(d[21]),"+f"(d[22]),"+f"(d[23]),"+f"(d[24]),"+f"(d[25]),"+f"(d[26]),"+f"(d[27]),"+f"(d[28]),"+f"(d[29]),"+f"(d[30]),"+f"(d[31]),"+f"(d[32]),"+f"(d[33]),"+f"(d[34]),"+f"(d[35]),"+f"(d[36]),"+f"(d[37]),"+f"(d[38]),"+f"(d[39]),"+f"(d[40]),"+f"(d[41]),"+f"(d[42]),"+f"(d[43]),"+f"(d[44]),"+f"(d[45]),"+f"(d[46]),"+f"(d[47]),"+f"(d[48]),"+f"(d[49]),"+f"(d[50]),"+f"(d[51]),"+f"(d[52]),"+f"(d[53]),"+f"(d[54]),"+f"(d[55]),"+f"(d[56]),"+f"(d[57]),"+f"(d[58]),"+f"(d[59]),"+f"(d[60]),"+f"(d[61]),"+f"(d[62]),"+f"(d[63])
    : "r"(alo), "r"(ahi), "r"(blo), "r"(bhi), "r"(sd), "n"(TA), "n"(TB)); }
  template<int TB> static __device__ __forceinline__ void rs(float* d, uint32_t a0, uint32_t a1, uint32_t a2, uint32_t a3, uint32_t blo, uint32_t bhi, int sd) {
  asm volatile("{ .reg .pred p; .reg .b64 db; mov.b64 db, {%68,%69}; setp.ne.b32 p, %71, 0;\n"
    "wgmma.mma_async.sync.aligned.m64n128k16.f32.bf16.bf16 {%0,%1,%2,%3,%4,%5,%6,%7,%8,%9,%10,%11,%12,%13,%14,%15,%16,%17,%18,%19,%20,%21,%22,%23,%24,%25,%26,%27,%28,%29,%30,%31,%32,%33,%34,%35,%36,%37,%38,%39,%40,%41,%42,%43,%44,%45,%46,%47,%48,%49,%50,%51,%52,%53,%54,%55,%56,%57,%58,%59,%60,%61,%62,%63}, {%64,%65,%66,%67}, db, p, 1, 1, %70; }"
    : "+f"(d[0]),"+f"(d[1]),"+f"(d[2]),"+f"(d[3]),"+f"(d[4]),"+f"(d[5]),"+f"(d[6]),"+f"(d[7]),"+f"(d[8]),"+f"(d[9]),"+f"(d[10]),"+f"(d[11]),"+f"(d[12]),"+f"(d[13]),"+f"(d[14]),"+f"(d[15]),"+f"(d[16]),"+f"(d[17]),"+f"(d[18]),"+f"(d[19]),"+f"(d[20]),"+f"(d[21]),"+f"(d[22]),"+f"(d[23]),"+f"(d[24]),"+f"(d[25]),"+f"(d[26]),"+f"(d[27]),"+f"(d[28]),"+f"(d[29]),"+f"(d[30]),"+f"(d[31]),"+f"(d[32]),"+f"(d[33]),"+f"(d[34]),"+f"(d[35]),"+f"(d[36]),"+f"(d[37]),"+f"(d[38]),"+f"(d[39]),"+f"(d[40]),"+f"(d[41]),"+f"(d[42]),"+f"(d[43]),"+f"(d[44]),"+f"(d[45]),"+f"(d[46]),"+f"(d[47]),"+f"(d[48]),"+f"(d[49]),"+f"(d[50]),"+f"(d[51]),"+f"(d[52]),"+f"(d[53]),"+f"(d[54]),"+f"(d[55]),"+f"(d[56]),"+f"(d[57]),"+f"(d[58]),"+f"(d[59]),"+f"(d[60]),"+f"(d[61]),"+f"(d[62]),"+f"(d[63])
    : "r"(a0), "r"(a1), "r"(a2), "r"(a3), "r"(blo), "r"(bhi), "n"(TB), "r"(sd)); }
};
template<> struct WG<144> { template<int TA, int TB> static __device__ __forceinline__ void ss(float* d, uint32_t alo, uint32_t ahi, uint32_t blo, uint32_t bhi, int sd) {
  asm volatile("{ .reg .pred p; .reg .b64 da, db; mov.b64 da, {%72,%73}; mov.b64 db, {%74,%75}; setp.ne.b32 p, %76, 0;\n"
    "wgmma.mma_async.sync.aligned.m64n144k16.f32.bf16.bf16 {%0,%1,%2,%3,%4,%5,%6,%7,%8,%9,%10,%11,%12,%13,%14,%15,%16,%17,%18,%19,%20,%21,%22,%23,%24,%25,%26,%27,%28,%29,%30,%31,%32,%33,%34,%35,%36,%37,%38,%39,%40,%41,%42,%43,%44,%45,%46,%47,%48,%49,%50,%51,%52,%53,%54,%55,%56,%57,%58,%59,%60,%61,%62,%63,%64,%65,%66,%67,%68,%69,%70,%71}, da, db, p, 1, 1, %77, %78; }"
    : "+f"(d[0]),"+f"(d[1]),"+f"(d[2]),"+f"(d[3]),"+f"(d[4]),"+f"(d[5]),"+f"(d[6]),"+f"(d[7]),"+f"(d[8]),"+f"(d[9]),"+f"(d[10]),"+f"(d[11]),"+f"(d[12]),"+f"(d[13]),"+f"(d[14]),"+f"(d[15]),"+f"(d[16]),"+f"(d[17]),"+f"(d[18]),"+f"(d[19]),"+f"(d[20]),"+f"(d[21]),"+f"(d[22]),"+f"(d[23]),"+f"(d[24]),"+f"(d[25]),"+f"(d[26]),"+f"(d[27]),"+f"(d[28]),"+f"(d[29]),"+f"(d[30]),"+f"(d[31]),"+f"(d[32]),"+f"(d[33]),"+f"(d[34]),"+f"(d[35]),"+f"(d[36]),"+f"(d[37]),"+f"(d[38]),"+f"(d[39]),"+f"(d[40]),"+f"(d[41]),"+f"(d[42]),"+f"(d[43]),"+f"(d[44]),"+f"(d[45]),"+f"(d[46]),"+f"(d[47]),"+f"(d[48]),"+f"(d[49]),"+f"(d[50]),"+f"(d[51]),"+f"(d[52]),"+f"(d[53]),"+f"(d[54]),"+f"(d[55]),"+f"(d[56]),"+f"(d[57]),"+f"(d[58]),"+f"(d[59]),"+f"(d[60]),"+f"(d[61]),"+f"(d[62]),"+f"(d[63]),"+f"(d[64]),"+f"(d[65]),"+f"(d[66]),"+f"(d[67]),"+f"(d[68]),"+f"(d[69]),"+f"(d[70]),"+f"(d[71])
    : "r"(alo), "r"(ahi), "r"(blo), "r"(bhi), "r"(sd), "n"(TA), "n"(TB)); }
  template<int TB> static __device__ __forceinline__ void rs(float* d, uint32_t a0, uint32_t a1, uint32_t a2, uint32_t a3, uint32_t blo, uint32_t bhi, int sd) {
  asm volatile("{ .reg .pred p; .reg .b64 db; mov.b64 db, {%76,%77}; setp.ne.b32 p, %79, 0;\n"
    "wgmma.mma_async.sync.aligned.m64n144k16.f32.bf16.bf16 {%0,%1,%2,%3,%4,%5,%6,%7,%8,%9,%10,%11,%12,%13,%14,%15,%16,%17,%18,%19,%20,%21,%22,%23,%24,%25,%26,%27,%28,%29,%30,%31,%32,%33,%34,%35,%36,%37,%38,%39,%40,%41,%42,%43,%44,%45,%46,%47,%48,%49,%50,%51,%52,%53,%54,%55,%56,%57,%58,%59,%60,%61,%62,%63,%64,%65,%66,%67,%68,%69,%70,%71}, {%72,%73,%74,%75}, db, p, 1, 1, %78; }"
    : "+f"(d[0]),"+f"(d[1]),"+f"(d[2]),"+f"(d[3]),"+f"(d[4]),"+f"(d[5]),"+f"(d[6]),"+f"(d[7]),"+f"(d[8]),"+f"(d[9]),"+f"(d[10]),"+f"(d[11]),"+f"(d[12]),"+f"(d[13]),"+f"(d[14]),"+f"(d[15]),"+f"(d[16]),"+f"(d[17]),"+f"(d[18]),"+f"(d[19]),"+f"(d[20]),"+f"(d[21]),"+f"(d[22]),"+f"(d[23]),"+f"(d[24]),"+f"(d[25]),"+f"(d[26]),"+f"(d[27]),"+f"(d[28]),"+f"(d[29]),"+f"(d[30]),"+f"(d[31]),"+f"(d[32]),"+f"(d[33]),"+f"(d[34]),"+f"(d[35]),"+f"(d[36]),"+f"(d[37]),"+f"(d[38]),"+f"(d[39]),"+f"(d[40]),"+f"(d[41]),"+f"(d[42]),"+f"(d[43]),"+f"(d[44]),"+f"(d[45]),"+f"(d[46]),"+f"(d[47]),"+f"(d[48]),"+f"(d[49]),"+f"(d[50]),"+f"(d[51]),"+f"(d[52]),"+f"(d[53]),"+f"(d[54]),"+f"(d[55]),"+f"(d[56]),"+f"(d[57]),"+f"(d[58]),"+f"(d[59]),"+f"(d[60]),"+f"(d[61]),"+f"(d[62]),"+f"(d[63]),"+f"(d[64]),"+f"(d[65]),"+f"(d[66]),"+f"(d[67]),"+f"(d[68]),"+f"(d[69]),"+f"(d[70]),"+f"(d[71])
    : "r"(a0), "r"(a1), "r"(a2), "r"(a3), "r"(blo), "r"(bhi), "n"(TB), "r"(sd)); }
};
template<> struct WG<160> { template<int TA, int TB> static __device__ __forceinline__ void ss(float* d, uint32_t alo, uint32_t ahi, uint32_t blo, uint32_t bhi, int sd) {
  asm volatile("{ .reg .pred p; .reg .b64 da, db; mov.b64 da, {%80,%81}; mov.b64 db, {%82,%83}; setp.ne.b32 p, %84, 0;\n"
    "wgmma.mma_async.sync.aligned.m64n160k16.f32.bf16.bf16 {%0,%1,%2,%3,%4,%5,%6,%7,%8,%9,%10,%11,%12,%13,%14,%15,%16,%17,%18,%19,%20,%21,%22,%23,%24,%25,%26,%27,%28,%29,%30,%31,%32,%33,%34,%35,%36,%37,%38,%39,%40,%41,%42,%43,%44,%45,%46,%47,%48,%49,%50,%51,%52,%53,%54,%55,%56,%57,%58,%59,%60,%61,%62,%63,%64,%65,%66,%67,%68,%69,%70,%71,%72,%73,%74,%75,%76,%77,%78,%79}, da, db, p, 1, 1, %85, %86; }"
    : "+f"(d[0]),"+f"(d[1]),"+f"(d[2]),"+f"(d[3]),"+f"(d[4]),"+f"(d[5]),"+f"(d[6]),"+f"(d[7]),"+f"(d[8]),"+f"(d[9]),"+f"(d[10]),"+f"(d[11]),"+f"(d[12]),"+f"(d[13]),"+f"(d[14]),"+f"(d[15]),"+f"(d[16]),"+f"(d[17]),"+f"(d[18]),"+f"(d[19]),"+f"(d[20]),"+f"(d[21]),"+f"(d[22]),"+f"(d[23]),"+f"(d[24]),"+f"(d[25]),"+f"(d[26]),"+f"(d[27]),"+f"(d[28]),"+f"(d[29]),"+f"(d[30]),"+f"(d[31]),"+f"(d[32]),"+f"(d[33]),"+f"(d[34]),"+f"(d[35]),"+f"(d[36]),"+f"(d[37]),"+f"(d[38]),"+f"(d[39]),"+f"(d[40]),"+f"(d[41]),"+f"(d[42]),"+f"(d[43]),"+f"(d[44]),"+f"(d[45]),"+f"(d[46]),"+f"(d[47]),"+f"(d[48]),"+f"(d[49]),"+f"(d[50]),"+f"(d[51]),"+f"(d[52]),"+f"(d[53]),"+f"(d[54]),"+f"(d[55]),"+f"(d[56]),"+f"(d[57]),"+f"(d[58]),"+f"(d[59]),"+f"(d[60]),"+f"(d[61]),"+f"(d[62]),"+f"(d[63]),"+f"(d[64]),"+f"(d[65]),"+f"(d[66]),"+f"(d[67]),"+f"(d[68]),"+f"(d[69]),"+f"(d[70]),"+f"(d[71]),"+f"(d[72]),"+f"(d[73]),"+f"(d[74]),"+f"(d[75]),"+f"(d[76]),"+f"(d[77]),"+f"(d[78]),"+f"(d[79])
    : "r"(alo), "r"(ahi), "r"(blo), "r"(bhi), "r"(sd), "n"(TA), "n"(TB)); }
  template<int TB> static __device__ __forceinline__ void rs(float* d, uint32_t a0, uint32_t a1, uint32_t a2, uint32_t a3, uint32_t blo, uint32_t bhi, int sd) {
  asm volatile("{ .reg .pred p; .reg .b64 db; mov.b64 db, {%84,%85}; setp.ne.b32 p, %87, 0;\n"
    "wgmma.mma_async.sync.aligned.m64n160k16.f32.bf16.bf16 {%0,%1,%2,%3,%4,%5,%6,%7,%8,%9,%10,%11,%12,%13,%14,%15,%16,%17,%18,%19,%20,%21,%22,%23,%24,%25,%26,%27,%28,%29,%30,%31,%32,%33,%34,%35,%36,%37,%38,%39,%40,%41,%42,%43,%44,%45,%46,%47,%48,%49,%50,%51,%52,%53,%54,%55,%56,%57,%58,%59,%60,%61,%62,%63,%64,%65,%66,%67,%68,%69,%70,%71,%72,%73,%74,%75,%76,%77,%78,%79}, {%80,%81,%82,%83}, db, p, 1, 1, %86; }"
    : "+f"(d[0]),"+f"(d[1]),"+f"(d[2]),"+f"(d[3]),"+f"(d[4]),"+f"(d[5]),"+f"(d[6]),"+f"(d[7]),"+f"(d[8]),"+f"(d[9]),"+f"(d[10]),"+f"(d[11]),"+f"(d[12]),"+f"(d[13]),"+f"(d[14]),"+f"(d[15]),"+f"(d[16]),"+f"(d[17]),"+f"(d[18]),"+f"(d[19]),"+f"(d[20]),"+f"(d[21]),"+f"(d[22]),"+f"(d[23]),"+f"(d[24]),"+f"(d[25]),"+f"(d[26]),"+f"(d[27]),"+f"(d[28]),"+f"(d[29]),"+f"(d[30]),"+f"(d[31]),"+f"(d[32]),"+f"(d[33]),"+f"(d[34]),"+f"(d[35]),"+f"(d[36]),"+f"(d[37]),"+f"(d[38]),"+f"(d[39]),"+f"(d[40]),"+f"(d[41]),"+f"(d[42]),"+f"(d[43]),"+f"(d[44]),"+f"(d[45]),"+f"(d[46]),"+f"(d[47]),"+f"(d[48]),"+f"(d[49]),"+f"(d[50]),"+f"(d[51]),"+f"(d[52]),"+f"(d[53]),"+f"(d[54]),"+f"(d[55]),"+f"(d[56]),"+f"(d[57]),"+f"(d[58]),"+f"(d[59]),"+f"(d[60]),"+f"(d[61]),"+f"(d[62]),"+f"(d[63]),"+f"(d[64]),"+f"(d[65]),"+f"(d[66]),"+f"(d[67]),"+f"(d[68]),"+f"(d[69]),"+f"(d[70]),"+f"(d[71]),"+f"(d[72]),"+f"(d[73]),"+f"(d[74]),"+f"(d[75]),"+f"(d[76]),"+f"(d[77]),"+f"(d[78]),"+f"(d[79])
    : "r"(a0), "r"(a1), "r"(a2), "r"(a3), "r"(blo), "r"(bhi), "n"(TB), "r"(sd)); }
};
template<> struct WG<176> { template<int TA, int TB> static __device__ __forceinline__ void ss(float* d, uint32_t alo, uint32_t ahi, uint32_t blo, uint32_t bhi, int sd) {
  asm volatile("{ .reg .pred p; .reg .b64 da, db; mov.b64 da, {%88,%89}; mov.b64 db, {%90,%91}; setp.ne.b32 p, %92, 0;\n"
    "wgmma.mma_async.sync.aligned.m64n176k16.f32.bf16.bf16 {%0,%1,%2,%3,%4,%5,%6,%7,%8,%9,%10,%11,%12,%13,%14,%15,%16,%17,%18,%19,%20,%21,%22,%23,%24,%25,%26,%27,%28,%29,%30,%31,%32,%33,%34,%35,%36,%37,%38,%39,%40,%41,%42,%43,%44,%45,%46,%47,%48,%49,%50,%51,%52,%53,%54,%55,%56,%57,%58,%59,%60,%61,%62,%63,%64,%65,%66,%67,%68,%69,%70,%71,%72,%73,%74,%75,%76,%77,%78,%79,%80,%81,%82,%83,%84,%85,%86,%87}, da, db, p, 1, 1, %93, %94; }"
    : "+f"(d[0]),"+f"(d[1]),"+f"(d[2]),"+f"(d[3]),"+f"(d[4]),"+f"(d[5]),"+f"(d[6]),"+f"(d[7]),"+f"(d[8]),"+f"(d[9]),"+f"(d[10]),"+f"(d[11]),"+f"(d[12]),"+f"(d[13]),"+f"(d[14]),"+f"(d[15]),"+f"(d[16]),"+f"(d[17]),"+f"(d[18]),"+f"(d[19]),"+f"(d[20]),"+f"(d[21]),"+f"(d[22]),"+f"(d[23]),"+f"(d[24]),"+f"(d[25]),"+f"(d[26]),"+f"(d[27]),"+f"(d[28]),"+f"(d[29]),"+f"(d[30]),"+f"(d[31]),"+f"(d[32]),"+f"(d[33]),"+f"(d[34]),"+f"(d[35]),"+f"(d[36]),"+f"(d[37]),"+f"(d[38]),"+f"(d[39]),"+f"(d[40]),"+f"(d[41]),"+f"(d[42]),"+f"(d[43]),"+f"(d[44]),"+f"(d[45]),"+f"(d[46]),"+f"(d[47]),"+f"(d[48]),"+f"(d[49]),"+f"(d[50]),"+f"(d[51]),"+f"(d[52]),"+f"(d[53]),"+f"(d[54]),"+f"(d[55]),"+f"(d[56]),"+f"(d[57]),"+f"(d[58]),"+f"(d[59]),"+f"(d[60]),"+f"(d[61]),"+f"(d[62]),"+f"(d[63]),"+f"(d[64]),"+f"(d[65]),"+f"(d[66]),"+f"(d[67]),"+f"(d[68]),"+f"(d[69]),"+f"(d[70]),"+f"(d[71]),"+f"(d[72]),"+f"(d[73]),"+f"(d[74]),"+f"(d[75]),"+f"(d[76]),"+f"(d[77]),"+f"(d[78]),"+f"(d[79]),"+f"(d[80]),"+f"(d[81]),"+f"(d[82]),"+f"(d[83]),"+f"(d[84]),"+f"(d[85]),"+f"(d[86]),"+f"(d[87])
    : "r"(alo), "r"(ahi), "r"(blo), "r"(bhi), "r"(sd), "n"(TA), "n"(TB)); }
  template<int TB> static __device__ __forceinline__ void rs(float* d, uint32_t a0, uint32_t a1, uint32_t a2, uint32_t a3, uint32_t blo, uint32_t bhi, int sd) {
  asm volatile("{ .reg .pred p; .reg .b64 db; mov.b64 db, {%92,%93}; setp.ne.b32 p, %95, 0;\n"
    "wgmma.mma_async.sync.aligned.m64n176k16.f32.bf16.bf16 {%0,%1,%2,%3,%4,%5,%6,%7,%8,%9,%10,%11,%12,%13,%14,%15,%16,%17,%18,%19,%20,%21,%22,%23,%24,%25,%26,%27,%28,%29,%30,%31,%32,%33,%34,%35,%36,%37,%38,%39,%40,%41,%42,%43,%44,%45,%46,%47,%48,%49,%50,%51,%52,%53,%54,%55,%56,%57,%58,%59,%60,%61,%62,%63,%64,%65,%66,%67,%68,%69,%70,%71,%72,%73,%74,%75,%76,%77,%78,%79,%80,%81,%82,%83,%84,%85,%86,%87}, {%88,%89,%90,%91}, db, p, 1, 1, %94; }"
    : "+f"(d[0]),"+f"(d[1]),"+f"(d[2]),"+f"(d[3]),"+f"(d[4]),"+f"(d[5]),"+f"(d[6]),"+f"(d[7]),"+f"(d[8]),"+f"(d[9]),"+f"(d[10]),"+f"(d[11]),"+f"(d[12]),"+f"(d[13]),"+f"(d[14]),"+f"(d[15]),"+f"(d[16]),"+f"(d[17]),"+f"(d[18]),"+f"(d[19]),"+f"(d[20]),"+f"(d[21]),"+f"(d[22]),"+f"(d[23]),"+f"(d[24]),"+f"(d[25]),"+f"(d[26]),"+f"(d[27]),"+f"(d[28]),"+f"(d[29]),"+f"(d[30]),"+f"(d[31]),"+f"(d[32]),"+f"(d[33]),"+f"(d[34]),"+f"(d[35]),"+f"(d[36]),"+f"(d[37]),"+f"(d[38]),"+f"(d[39]),"+f"(d[40]),"+f"(d[41]),"+f"(d[42]),"+f"(d[43]),"+f"(d[44]),"+f"(d[45]),"+f"(d[46]),"+f"(d[47]),"+f"(d[48]),"+f"(d[49]),"+f"(d[50]),"+f"(d[51]),"+f"(d[52]),"+f"(d[53]),"+f"(d[54]),"+f"(d[55]),"+f"(d[56]),"+f"(d[57]),"+f"(d[58]),"+f"(d[59]),"+f"(d[60]),"+f"(d[61]),"+f"(d[62]),"+f"(d[63]),"+f"(d[64]),"+f"(d[65]),"+f"(d[66]),"+f"(d[67]),"+f"(d[68]),"+f"(d[69]),"+f"(d[70]),"+f"(d[71]),"+f"(d[72]),"+f"(d[73]),"+f"(d[74]),"+f"(d[75]),"+f"(d[76]),"+f"(d[77]),"+f"(d[78]),"+f"(d[79]),"+f"(d[80]),"+f"(d[81]),"+f"(d[82]),"+f"(d[83]),"+f"(d[84]),"+f"(d[85]),"+f"(d[86]),"+f"(d[87])
    : "r"(a0), "r"(a1), "r"(a2), "r"(a3), "r"(blo), "r"(bhi), "n"(TB), "r"(sd)); }
};
template<> struct WG<192> { template<int TA, int TB> static __device__ __forceinline__ void ss(float* d, uint32_t alo, uint32_t ahi, uint32_t blo, uint32_t bhi, int sd) {
  asm volatile("{ .reg .pred p; .reg .b64 da, db; mov.b64 da, {%96,%97}; mov.b64 db, {%98,%99}; setp.ne.b32 p, %100, 0;\n"
    "wgmma.mma_async.sync.aligned.m64n192k16.f32.bf16.bf16 {%0,%1,%2,%3,%4,%5,%6,%7,%8,%9,%10,%11,%12,%13,%14,%15,%16,%17,%18,%19,%20,%21,%22,%23,%24,%25,%26,%27,%28,%29,%30,%31,%32,%33,%34,%35,%36,%37,%38,%39,%40,%41,%42,%43,%44,%45,%46,%47,%48,%49,%50,%51,%52,%53,%54,%55,%56,%57,%58,%59,%60,%61,%62,%63,%64,%65,%66,%67,%68,%69,%70,%71,%72,%73,%74,%75,%76,%77,%78,%79,%80,%81,%82,%83,%84,%85,%86,%87,%88,%89,%90,%91,%92,%93,%94,%95}, da, db, p, 1, 1, %101, %102; }"
    : "+f"(d[0]),"+f"(d[1]),"+f"(d[2]),"+f"(d[3]),"+f"(d[4]),"+f"(d[5]),"+f"(d[6]),"+f"(d[7]),"+f"(d[8]),"+f"(d[9]),"+f"(d[10]),"+f"(d[11]),"+f"(d[12]),"+f"(d[13]),"+f"(d[14]),"+f"(d[15]),"+f"(d[16]),"+f"(d[17]),"+f"(d[18]),"+f"(d[19]),"+f"(d[20]),"+f"(d[21]),"+f"(d[22]),"+f"(d[23]),"+f"(d[24]),"+f"(d[25]),"+f"(d[26]),"+f"(d[27]),"+f"(d[28]),"+f"(d[29]),"+f"(d[30]),"+f"(d[31]),"+f"(d[32]),"+f"(d[33]),"+f"(d[34]),"+f"(d[35]),"+f"(d[36]),"+f"(d[37]),"+f"(d[38]),"+f"(d[39]),"+f"(d[40]),"+f"(d[41]),"+f"(d[42]),"+f"(d[43]),"+f"(d[44]),"+f"(d[45]),"+f"(d[46]),"+f"(d[47]),"+f"(d[48]),"+f"(d[49]),"+f"(d[50]),"+f"(d[51]),"+f"(d[52]),"+f"(d[53]),"+f"(d[54]),"+f"(d[55]),"+f"(d[56]),"+f"(d[57]),"+f"(d[58]),"+f"(d[59]),"+f"(d[60]),"+f"(d[61]),"+f"(d[62]),"+f"(d[63]),"+f"(d[64]),"+f"(d[65]),"+f"(d[66]),"+f"(d[67]),"+f"(d[68]),"+f"(d[69]),"+f"(d[70]),"+f"(d[71]),"+f"(d[72]),"+f"(d[73]),"+f"(d[74]),"+f"(d[75]),"+f"(d[76]),"+f"(d[77]),"+f"(d[78]),"+f"(d[79]),"+f"(d[80]),"+f"(d[81]),"+f"(d[82]),"+f"(d[83]),"+f"(d[84]),"+f"(d[85]),"+f"(d[86]),"+f"(d[87]),"+f"(d[88]),"+f"(d[89]),"+f"(d[90]),"+f"(d[91]),"+f"(d[92]),"+f"(d[93]),"+f"(d[94]),"+f"(d[95])
    : "r"(alo), "r"(ahi), "r"(blo), "r"(bhi), "r"(sd), "n"(TA), "n"(TB)); }
  template<int TB> static __device__ __forceinline__ void rs(float* d, uint32_t a0, uint32_t a1, uint32_t a2, uint32_t a3, uint32_t blo, uint32_t bhi, int sd) {
  asm volatile("{ .reg .pred p; .reg .b64 db; mov.b64 db, {%100,%101}; setp.ne.b32 p, %103, 0;\n"
    "wgmma.mma_async.sync.aligned.m64n192k16.f32.bf16.bf16 {%0,%1,%2,%3,%4,%5,%6,%7,%8,%9,%10,%11,%12,%13,%14,%15,%16,%17,%18,%19,%20,%21,%22,%23,%24,%25,%26,%27,%28,%29,%30,%31,%32,%33,%34,%35,%36,%37,%38,%39,%40,%41,%42,%43,%44,%45,%46,%47,%48,%49,%50,%51,%52,%53,%54,%55,%56,%57,%58,%59,%60,%61,%62,%63,%64,%65,%66,%67,%68,%69,%70,%71,%72,%73,%74,%75,%76,%77,%78,%79,%80,%81,%82,%83,%84,%85,%86,%87,%88,%89,%90,%91,%92,%93,%94,%95}, {%96,%97,%98,%99}, db, p, 1, 1, %102; }"
    : "+f"(d[0]),"+f"(d[1]),"+f"(d[2]),"+f"(d[3]),"+f"(d[4]),"+f"(d[5]),"+f"(d[6]),"+f"(d[7]),"+f"(d[8]),"+f"(d[9]),"+f"(d[10]),"+f"(d[11]),"+f"(d[12]),"+f"(d[13]),"+f"(d[14]),"+f"(d[15]),"+f"(d[16]),"+f"(d[17]),"+f"(d[18]),"+f"(d[19]),"+f"(d[20]),"+f"(d[21]),"+f"(d[22]),"+f"(d[23]),"+f"(d[24]),"+f"(d[25]),"+f"(d[26]),"+f"(d[27]),"+f"(d[28]),"+f"(d[29]),"+f"(d[30]),"+f"(d[31]),"+f"(d[32]),"+f"(d[33]),"+f"(d[34]),"+f"(d[35]),"+f"(d[36]),"+f"(d[37]),"+f"(d[38]),"+f"(d[39]),"+f"(d[40]),"+f"(d[41]),"+f"(d[42]),"+f"(d[43]),"+f"(d[44]),"+f"(d[45]),"+f"(d[46]),"+f"(d[47]),"+f"(d[48]),"+f"(d[49]),"+f"(d[50]),"+f"(d[51]),"+f"(d[52]),"+f"(d[53]),"+f"(d[54]),"+f"(d[55]),"+f"(d[56]),"+f"(d[57]),"+f"(d[58]),"+f"(d[59]),"+f"(d[60]),"+f"(d[61]),"+f"(d[62]),"+f"(d[63]),"+f"(d[64]),"+f"(d[65]),"+f"(d[66]),"+f"(d[67]),"+f"(d[68]),"+f"(d[69]),"+f"(d[70]),"+f"(d[71]),"+f"(d[72]),"+f"(d[73]),"+f"(d[74]),"+f"(d[75]),"+f"(d[76]),"+f"(d[77]),"+f"(d[78]),"+f"(d[79]),"+f"(d[80]),"+f"(d[81]),"+f"(d[82]),"+f"(d[83]),"+f"(d[84]),"+f"(d[85]),"+f"(d[86]),"+f"(d[87]),"+f"(d[88]),"+f"(d[89]),"+f"(d[90]),"+f"(d[91]),"+f"(d[92]),"+f"(d[93]),"+f"(d[94]),"+f"(d[95])
    : "r"(a0), "r"(a1), "r"(a2), "r"(a3), "r"(blo), "r"(bhi), "n"(TB), "r"(sd)); }
};
template<> struct WG<208> { template<int TA, int TB> static __device__ __forceinline__ void ss(float* d, uint32_t alo, uint32_t ahi, uint32_t blo, uint32_t bhi, int sd) {
  asm volatile("{ .reg .pred p; .reg .b64 da, db; mov.b64 da, {%104,%105}; mov.b64 db, {%106,%107}; setp.ne.b32 p, %108, 0;\n"
    "wgmma.mma_async.sync.aligned.m64n208k16.f32.bf16.bf16 {%0,%1,%2,%3,%4,%5,%6,%7,%8,%9,%10,%11,%12,%13,%14,%15,%16,%17,%18,%19,%20,%21,%22,%23,%24,%25,%26,%27,%28,%29,%30,%31,%32,%33,%34,%35,%36,%37,%38,%39,%40,%41,%42,%43,%44,%45,%46,%47,%48,%49,%50,%51,%52,%53,%54,%55,%56,%57,%58,%59,%60,%61,%62,%63,%64,%65,%66,%67,%68,%69,%70,%71,%72,%73,%74,%75,%76,%77,%78,%79,%80,%81,%82,%83,%84,%85,%86,%87,%88,%89,%90,%91,%92,%93,%94,%95,%96,%97,%98,%99,%100,%101,%102,%103}, da, db, p, 1, 1, %109, %110; }"
    : "+f"(d[0]),"+f"(d[1]),"+f"(d[2]),"+f"(d[3]),"+f"(d[4]),"+f"(d[5]),"+f"(d[6]),"+f"(d[7]),"+f"(d[8]),"+f"(d[9]),"+f"(d[10]),"+f"(d[11]),"+f"(d[12]),"+f"(d[13]),"+f"(d[14]),"+f"(d[15]),"+f"(d[16]),"+f"(d[17]),"+f"(d[18]),"+f"(d[19]),"+f"(d[20]),"+f"(d[21]),"+f"(d[22]),"+f"(d[23]),"+f"(d[24]),"+f"(d[25]),"+f"(d[26]),"+f"(d[27]),"+f"(d[28]),"+f"(d[29]),"+f"(d[30]),"+f"(d[31]),"+f"(d[32]),"+f"(d[33]),"+f"(d[34]),"+f"(d[35]),"+f"(d[36]),"+f"(d[37]),"+f"(d[38]),"+f"(d[39]),"+f"(d[40]),"+f"(d[41]),"+f"(d[42]),"+f"(d[43]),"+f"(d[44]),"+f"(d[45]),"+f"(d[46]),"+f"(d[47]),"+f"(d[48]),"+f"(d[49]),"+f"(d[50]),"+f"(d[51]),"+f"(d[52]),"+f"(d[53]),"+f"(d[54]),"+f"(d[55]),"+f"(d[56]),"+f"(d[57]),"+f"(d[58]),"+f"(d[59]),"+f"(d[60]),"+f"(d[61]),"+f"(d[62]),"+f"(d[63]),"+f"(d[64]),"+f"(d[65]),"+f"(d[66]),"+f"(d[67]),"+f"(d[68]),"+f"(d[69]),"+f"(d[70]),"+f"(d[71]),"+f"(d[72]),"+f"(d[73]),"+f"(d[74]),"+f"(d[75]),"+f"(d[76]),"+f"(d[77]),"+f"(d[78]),"+f"(d[79]),"+f"(d[80]),"+f"(d[81]),"+f"(d[82]),"+f"(d[83]),"+f"(d[84]),"+f"(d[85]),"+f"(d[86]),"+f"(d[87]),"+f"(d[88]),"+f"(d[89]),"+f"(d[90]),"+f"(d[91]),"+f"(d[92]),"+f"(d[93]),"+f"(d[94]),"+f"(d[95]),"+f"(d[96]),"+f"(d[97]),"+f"(d[98]),"+f"(d[99]),"+f"(d[100]),"+f"(d[101]),"+f"(d[102]),"+f"(d[103])
    : "r"(alo), "r"(ahi), "r"(blo), "r"(bhi), "r"(sd), "n"(TA), "n"(TB)); }
  template<int TB> static __device__ __forceinline__ void rs(float* d, uint32_t a0, uint32_t a1, uint32_t a2, uint32_t a3, uint32_t blo, uint32_t bhi, int sd) {
  asm volatile("{ .reg .pred p; .reg .b64 db; mov.b64 db, {%108,%109}; setp.ne.b32 p, %111, 0;\n"
    "wgmma.mma_async.sync.aligned.m64n208k16.f32.bf16.bf16 {%0,%1,%2,%3,%4,%5,%6,%7,%8,%9,%10,%11,%12,%13,%14,%15,%16,%17,%18,%19,%20,%21,%22,%23,%24,%25,%26,%27,%28,%29,%30,%31,%32,%33,%34,%35,%36,%37,%38,%39,%40,%41,%42,%43,%44,%45,%46,%47,%48,%49,%50,%51,%52,%53,%54,%55,%56,%57,%58,%59,%60,%61,%62,%63,%64,%65,%66,%67,%68,%69,%70,%71,%72,%73,%74,%75,%76,%77,%78,%79,%80,%81,%82,%83,%84,%85,%86,%87,%88,%89,%90,%91,%92,%93,%94,%95,%96,%97,%98,%99,%100,%101,%102,%103}, {%104,%105,%106,%107}, db, p, 1, 1, %110; }"
    : "+f"(d[0]),"+f"(d[1]),"+f"(d[2]),"+f"(d[3]),"+f"(d[4]),"+f"(d[5]),"+f"(d[6]),"+f"(d[7]),"+f"(d[8]),"+f"(d[9]),"+f"(d[10]),"+f"(d[11]),"+f"(d[12]),"+f"(d[13]),"+f"(d[14]),"+f"(d[15]),"+f"(d[16]),"+f"(d[17]),"+f"(d[18]),"+f"(d[19]),"+f"(d[20]),"+f"(d[21]),"+f"(d[22]),"+f"(d[23]),"+f"(d[24]),"+f"(d[25]),"+f"(d[26]),"+f"(d[27]),"+f"(d[28]),"+f"(d[29]),"+f"(d[30]),"+f"(d[31]),"+f"(d[32]),"+f"(d[33]),"+f"(d[34]),"+f"(d[35]),"+f"(d[36]),"+f"(d[37]),"+f"(d[38]),"+f"(d[39]),"+f"(d[40]),"+f"(d[41]),"+f"(d[42]),"+f"(d[43]),"+f"(d[44]),"+f"(d[45]),"+f"(d[46]),"+f"(d[47]),"+f"(d[48]),"+f"(d[49]),"+f"(d[50]),"+f"(d[51]),"+f"(d[52]),"+f"(d[53]),"+f"(d[54]),"+f"(d[55]),"+f"(d[56]),"+f"(d[57]),"+f"(d[58]),"+f"(d[59]),"+f"(d[60]),"+f"(d[61]),"+f"(d[62]),"+f"(d[63]),"+f"(d[64]),"+f"(d[65]),"+f"(d[66]),"+f"(d[67]),"+f"(d[68]),"+f"(d[69]),"+f"(d[70]),"+f"(d[71]),"+f"(d[72]),"+f"(d[73]),"+f"(d[74]),"+f"(d[75]),"+f"(d[76]),"+f"(d[77]),"+f"(d[78]),"+f"(d[79]),"+f"(d[80]),"+f"(d[81]),"+f"(d[82]),"+f"(d[83]),"+f"(d[84]),"+f"(d[85]),"+f"(d[86]),"+f"(d[87]),"+f"(d[88]),"+f"(d[89]),"+f"(d[90]),"+f"(d[91]),"+f"(d[92]),"+f"(d[93]),"+f"(d[94]),"+f"(d[95]),"+f"(d[96]),"+f"(d[97]),"+f"(d[98]),"+f"(d[99]),"+f"(d[100]),"+f"(d[101]),"+f"(d[102]),"+f"(d[103])
    : "r"(a0), "r"(a1), "r"(a2), "r"(a3), "r"(blo), "r"(bhi), "n"(TB), "r"(sd)); }
};
template<> struct WG<224> { template<int TA, int TB> static __device__ __forceinline__ void ss(float* d, uint32_t alo, uint32_t ahi, uint32_t blo, uint32_t bhi, int sd) {
  asm volatile("{ .reg .pred p; .reg .b64 da, db; mov.b64 da, {%112,%113}; mov.b64 db, {%114,%115}; setp.ne.b32 p, %116, 0;\n"
    "wgmma.mma_async.sync.aligned.m64n224k16.f32.bf16.bf16 {%0,%1,%2,%3,%4,%5,%6,%7,%8,%9,%10,%11,%12,%13,%14,%15,%16,%17,%18,%19,%20,%21,%22,%23,%24,%25,%26,%27,%28,%29,%30,%31,%32,%33,%34,%35,%36,%37,%38,%39,%40,%41,%42,%43,%44,%45,%46,%47,%48,%49,%50,%51,%52,%53,%54,%55,%56,%57,%58,%59,%60,%61,%62,%63,%64,%65,%66,%67,%68,%69,%70,%71,%72,%73,%74,%75,%76,%77,%78,%79,%80,%81,%82,%83,%84,%85,%86,%87,%88,%89,%90,%91,%92,%93,%94,%95,%96,%97,%98,%99,%100,%101,%102,%103,%104,%105,%106,%107,%108,%109,%110,%111}, da, db, p, 1, 1, %117, %118; }"
    : "+f"(d[0]),"+f"(d[1]),"+f"(d[2]),"+f"(d[3]),"+f"(d[4]),"+f"(d[5]),"+f"(d[6]),"+f"(d[7]),"+f"(d[8]),"+f"(d[9]),"+f"(d[10]),"+f"(d[11]),"+f"(d[12]),"+f"(d[13]),"+f"(d[14]),"+f"(d[15]),"+f"(d[16]),"+f"(d[17]),"+f"(d[18]),"+f"(d[19]),"+f"(d[20]),"+f"(d[21]),"+f"(d[22]),"+f"(d[23]),"+f"(d[24]),"+f"(d[25]),"+f"(d[26]),"+f"(d[27]),"+f"(d[28]),"+f"(d[29]),"+f"(d[30]),"+f"(d[31]),"+f"(d[32]),"+f"(d[33]),"+f"(d[34]),"+f"(d[35]),"+f"(d[36]),"+f"(d[37]),"+f"(d[38]),"+f"(d[39]),"+f"(d[40]),"+f"(d[41]),"+f"(d[42]),"+f"(d[43]),"+f"(d[44]),"+f"(d[45]),"+f"(d[46]),"+f"(d[47]),"+f"(d[48]),"+f"(d[49]),"+f"(d[50]),"+f"(d[51]),"+f"(d[52]),"+f"(d[53]),"+f"(d[54]),"+f"(d[55]),"+f"(d[56]),"+f"(d[57]),"+f"(d[58]),"+f"(d[59]),"+f"(d[60]),"+f"(d[61]),"+f"(d[62]),"+f"(d[63]),"+f"(d[64]),"+f"(d[65]),"+f"(d[66]),"+f"(d[67]),"+f"(d[68]),"+f"(d[69]),"+f"(d[70]),"+f"(d[71]),"+f"(d[72]),"+f"(d[73]),"+f"(d[74]),"+f"(d[75]),"+f"(d[76]),"+f"(d[77]),"+f"(d[78]),"+f"(d[79]),"+f"(d[80]),"+f"(d[81]),"+f"(d[82]),"+f"(d[83]),"+f"(d[84]),"+f"(d[85]),"+f"(d[86]),"+f"(d[87]),"+f"(d[88]),"+f"(d[89]),"+f"(d[90]),"+f"(d[91]),"+f"(d[92]),"+f"(d[93]),"+f"(d[94]),"+f"(d[95]),"+f"(d[96]),"+f"(d[97]),"+f"(d[98]),"+f"(d[99]),"+f"(d[100]),"+f"(d[101]),"+f"(d[102]),"+f"(d[103]),"+f"(d[104]),"+f"(d[105]),"+f"(d[106]),"+f"(d[107]),"+f"(d[108]),"+f"(d[109]),"+f"(d[110]),"+f"(d[111])
    : "r"(alo), "r"(ahi), "r"(blo), "r"(bhi), "r"(sd), "n"(TA), "n"(TB)); }
  template<int TB> static __device__ __forceinline__ void rs(float* d, uint32_t a0, uint32_t a1, uint32_t a2, uint32_t a3, uint32_t blo, uint32_t bhi, int sd) {
  asm volatile("{ .reg .pred p; .reg .b64 db; mov.b64 db, {%116,%117}; setp.ne.b32 p, %119, 0;\n"
    "wgmma.mma_async.sync.aligned.m64n224k16.f32.bf16.bf16 {%0,%1,%2,%3,%4,%5,%6,%7,%8,%9,%10,%11,%12,%13,%14,%15,%16,%17,%18,%19,%20,%21,%22,%23,%24,%25,%26,%27,%28,%29,%30,%31,%32,%33,%34,%35,%36,%37,%38,%39,%40,%41,%42,%43,%44,%45,%46,%47,%48,%49,%50,%51,%52,%53,%54,%55,%56,%57,%58,%59,%60,%61,%62,%63,%64,%65,%66,%67,%68,%69,%70,%71,%72,%73,%74,%75,%76,%77,%78,%79,%80,%81,%82,%83,%84,%85,%86,%87,%88,%89,%90,%91,%92,%93,%94,%95,%96,%97,%98,%99,%100,%101,%102,%103,%104,%105,%106,%107,%108,%109,%110,%111}, {%112,%113,%114,%115}, db, p, 1, 1, %118; }"
    : "+f"(d[0]),"+f"(d[1]),"+f"(d[2]),"+f"(d[3]),"+f"(d[4]),"+f"(d[5]),"+f"(d[6]),"+f"(d[7]),"+f"(d[8]),"+f"(d[9]),"+f"(d[10]),"+f"(d[11]),"+f"(d[12]),"+f"(d[13]),"+f"(d[14]),"+f"(d[15]),"+f"(d[16]),"+f"(d[17]),"+f"(d[18]),"+f"(d[19]),"+f"(d[20]),"+f"(d[21]),"+f"(d[22]),"+f"(d[23]),"+f"(d[24]),"+f"(d[25]),"+f"(d[26]),"+f"(d[27]),"+f"(d[28]),"+f"(d[29]),"+f"(d[30]),"+f"(d[31]),"+f"(d[32]),"+f"(d[33]),"+f"(d[34]),"+f"(d[35]),"+f"(d[36]),"+f"(d[37]),"+f"(d[38]),"+f"(d[39]),"+f"(d[40]),"+f"(d[41]),"+f"(d[42]),"+f"(d[43]),"+f"(d[44]),"+f"(d[45]),"+f"(d[46]),"+f"(d[47]),"+f"(d[48]),"+f"(d[49]),"+f"(d[50]),"+f"(d[51]),"+f"(d[52]),"+f"(d[53]),"+f"(d[54]),"+f"(d[55]),"+f"(d[56]),"+f"(d[57]),"+f"(d[58]),"+f"(d[59]),"+f"(d[60]),"+f"(d[61]),"+f"(d[62]),"+f"(d[63]),"+f"(d[64]),"+f"(d[65]),"+f"(d[66]),"+f"(d[67]),"+f"(d[68]),"+f"(d[69]),"+f"(d[70]),"+f"(d[71]),"+f"(d[72]),"+f"(d[73]),"+f"(d[74]),"+f"(d[75]),"+f"(d[76]),"+f"(d[77]),"+f"(d[78]),"+f"(d[79]),"+f"(d[80]),"+f"(d[81]),"+f"(d[82]),"+f"(d[83]),"+f"(d[84]),"+f"(d[85]),"+f"(d[86]),"+f"(d[87]),"+f"(d[88]),"+f"(d[89]),"+f"(d[90]),"+f"(d[91]),"+f"(d[92]),"+f"(d[93]),"+f"(d[94]),"+f"(d[95]),"+f"(d[96]),"+f"(d[97]),"+f"(d[98]),"+f"(d[99]),"+f"(d[100]),"+f"(d[101]),"+f"(d[102]),"+f"(d[103]),"+f"(d[104]),"+f"(d[105]),"+f"(d[106]),"+f"(d[107]),"+f"(d[108]),"+f"(d[109]),"+f"(d[110]),"+f"(d[111])
    : "r"(a0), "r"(a1), "r"(a2), "r"(a3), "r"(blo), "r"(bhi), "n"(TB), "r"(sd)); }
};
template<> struct WG<240> { template<int TA, int TB> static __device__ __forceinline__ void ss(float* d, uint32_t alo, uint32_t ahi, uint32_t blo, uint32_t bhi, int sd) {
  asm volatile("{ .reg .pred p; .reg .b64 da, db; mov.b64 da, {%120,%121}; mov.b64 db, {%122,%123}; setp.ne.b32 p, %124, 0;\n"
    "wgmma.mma_async.sync.aligned.m64n240k16.f32.bf16.bf16 {%0,%1,%2,%3,%4,%5,%6,%7,%8,%9,%10,%11,%12,%13,%14,%15,%16,%17,%18,%19,%20,%21,%22,%23,%24,%25,%26,%27,%28,%29,%30,%31,%32,%33,%34,%35,%36,%37,%38,%39,%40,%41,%42,%43,%44,%45,%46,%47,%48,%49,%50,%51,%52,%53,%54,%55,%56,%57,%58,%59,%60,%61,%62,%63,%64,%65,%66,%67,%68,%69,%70,%71,%72,%73,%74,%75,%76,%77,%78,%79,%80,%81,%82,%83,%84,%85,%86,%87,%88,%89,%90,%91,%92,%93,%94,%95,%96,%97,%98,%99,%100,%101,%102,%103,%104,%105,%106,%107,%108,%109,%110,%111,%112,%113,%114,%115,%116,%117,%118,%119}, da, db, p, 1, 1, %125, %126; }"
    : "+f"(d[0]),"+f"(d[1]),"+f"(d[2]),"+f"(d[3]),"+f"(d[4]),"+f"(d[5]),"+f"(d[6]),"+f"(d[7]),"+f"(d[8]),"+f"(d[9]),"+f"(d[10]),"+f"(d[11]),"+f"(d[12]),"+f"(d[13]),"+f"(d[14]),"+f"(d[15]),"+f"(d[16]),"+f"(d[17]),"+f"(d[18]),"+f"(d[19]),"+f"(d[20]),"+f"(d[21]),"+f"(d[22]),"+f"(d[23]),"+f"(d[24]),"+f"(d[25]),"+f"(d[26]),"+f"(d[27]),"+f"(d[28]),"+f"(d[29]),"+f"(d[30]),"+f"(d[31]),"+f"(d[32]),"+f"(d[33]),"+f"(d[34]),"+f"(d[35]),"+f"(d[36]),"+f"(d[37]),"+f"(d[38]),"+f"(d[39]),"+f"(d[40]),"+f"(d[41]),"+f"(d[42]),"+f"(d[43]),"+f"(d[44]),"+f"(d[45]),"+f"(d[46]),"+f"(d[47]),"+f"(d[48]),"+f"(d[49]),"+f"(d[50]),"+f"(d[51]),"+f"(d[52]),"+f"(d[53]),"+f"(d[54]),"+f"(d[55]),"+f"(d[56]),"+f"(d[57]),"+f"(d[58]),"+f"(d[59]),"+f"(d[60]),"+f"(d[61]),"+f"(d[62]),"+f"(d[63]),"+f"(d[64]),"+f"(d[65]),"+f"(d[66]),"+f"(d[67]),"+f"(d[68]),"+f"(d[69]),"+f"(d[70]),"+f"(d[71]),"+f"(d[72]),"+f"(d[73]),"+f"(d[74]),"+f"(d[75]),"+f"(d[76]),"+f"(d[77]),"+f"(d[78]),"+f"(d[79]),"+f"(d[80]),"+f"(d[81]),"+f"(d[82]),"+f"(d[83]),"+f"(d[84]),"+f"(d[85]),"+f"(d[86]),"+f"(d[87]),"+f"(d[88]),"+f"(d[89]),"+f"(d[90]),"+f"(d[91]),"+f"(d[92]),"+f"(d[93]),"+f"(d[94]),"+f"(d[95]),"+f"(d[96]),"+f"(d[97]),"+f"(d[98]),"+f"(d[99]),"+f"(d[100]),"+f"(d[101]),"+f"(d[102]),"+f"(d[103]),"+f"(d[104]),"+f"(d[105]),"+f"(d[106]),"+f"(d[107]),"+f"(d[108]),"+f"(d[109]),"+f"(d[110]),"+f"(d[111]),"+f"(d[112]),"+f"(d[113]),"+f"(d[114]),"+f"(d[115]),"+f"(d[116]),"+f"(d[117]),"+f"(d[118]),"+f"(d[119])
    : "r"(alo), "r"(ahi), "r"(blo), "r"(bhi), "r"(sd), "n"(TA), "n"(TB)); }
  template<int TB> static __device__ __forceinline__ void rs(float* d, uint32_t a0, uint32_t a1, uint32_t a2, uint32_t a3, uint32_t blo, uint32_t bhi, int sd) {
  asm volatile("{ .reg .pred p; .reg .b64 db; mov.b64 db, {%124,%125}; setp.ne.b32 p, %127, 0;\n"
    "wgmma.mma_async.sync.aligned.m64n240k16.f32.bf16.bf16 {%0,%1,%2,%3,%4,%5,%6,%7,%8,%9,%10,%11,%12,%13,%14,%15,%16,%17,%18,%19,%20,%21,%22,%23,%24,%25,%26,%27,%28,%29,%30,%31,%32,%33,%34,%35,%36,%37,%38,%39,%40,%41,%42,%43,%44,%45,%46,%47,%48,%49,%50,%51,%52,%53,%54,%55,%56,%57,%58,%59,%60,%61,%62,%63,%64,%65,%66,%67,%68,%69,%70,%71,%72,%73,%74,%75,%76,%77,%78,%79,%80,%81,%82,%83,%84,%85,%86,%87,%88,%89,%90,%91,%92,%93,%94,%95,%96,%97,%98,%99,%100,%101,%102,%103,%104,%105,%106,%107,%108,%109,%110,%111,%112,%113,%114,%115,%116,%117,%118,%119}, {%120,%121,%122,%123}, db, p, 1, 1, %126; }"
    : "+f"(d[0]),"+f"(d[1]),"+f"(d[2]),"+f"(d[3]),"+f"(d[4]),"+f"(d[5]),"+f"(d[6]),"+f"(d[7]),"+f"(d[8]),"+f"(d[9]),"+f"(d[10]),"+f"(d[11]),"+f"(d[12]),"+f"(d[13]),"+f"(d[14]),"+f"(d[15]),"+f"(d[16]),"+f"(d[17]),"+f"(d[18]),"+f"(d[19]),"+f"(d[20]),"+f"(d[21]),"+f"(d[22]),"+f"(d[23]),"+f"(d[24]),"+f"(d[25]),"+f"(d[26]),"+f"(d[27]),"+f"(d[28]),"+f"(d[29]),"+f"(d[30]),"+f"(d[31]),"+f"(d[32]),"+f"(d[33]),"+f"(d[34]),"+f"(d[35]),"+f"(d[36]),"+f"(d[37]),"+f"(d[38]),"+f"(d[39]),"+f"(d[40]),"+f"(d[41]),"+f"(d[42]),"+f"(d[43]),"+f"(d[44]),"+f"(d[45]),"+f"(d[46]),"+f"(d[47]),"+f"(d[48]),"+f"(d[49]),"+f"(d[50]),"+f"(d[51]),"+f"(d[52]),"+f"(d[53]),"+f"(d[54]),"+f"(d[55]),"+f"(d[56]),"+f"(d[57]),"+f"(d[58]),"+f"(d[59]),"+f"(d[60]),"+f"(d[61]),"+f"(d[62]),"+f"(d[63]),"+f"(d[64]),"+f"(d[65]),"+f"(d[66]),"+f"(d[67]),"+f"(d[68]),"+f"(d[69]),"+f"(d[70]),"+f"(d[71]),"+f"(d[72]),"+f"(d[73]),"+f"(d[74]),"+f"(d[75]),"+f"(d[76]),"+f"(d[77]),"+f"(d[78]),"+f"(d[79]),"+f"(d[80]),"+f"(d[81]),"+f"(d[82]),"+f"(d[83]),"+f"(d[84]),"+f"(d[85]),"+f"(d[86]),"+f"(d[87]),"+f"(d[88]),"+f"(d[89]),"+f"(d[90]),"+f"(d[91]),"+f"(d[92]),"+f"(d[93]),"+f"(d[94]),"+f"(d[95]),"+f"(d[96]),"+f"(d[97]),"+f"(d[98]),"+f"(d[99]),"+f"(d[100]),"+f"(d[101]),"+f"(d[102]),"+f"(d[103]),"+f"(d[104]),"+f"(d[105]),"+f"(d[106]),"+f"(d[107]),"+f"(d[108]),"+f"(d[109]),"+f"(d[110]),"+f"(d[111]),"+f"(d[112]),"+f"(d[113]),"+f"(d[114]),"+f"(d[115]),"+f"(d[116]),"+f"(d[117]),"+f"(d[118]),"+f"(d[119])
    : "r"(a0), "r"(a1), "r"(a2), "r"(a3), "r"(blo), "r"(bhi), "n"(TB), "r"(sd)); }
};
template<> struct WG<256> { template<int TA, int TB> static __device__ __forceinline__ void ss(float* d, uint32_t alo, uint32_t ahi, uint32_t blo, uint32_t bhi, int sd) {
  asm volatile("{ .reg .pred p; .reg .b64 da, db; mov.b64 da, {%128,%129}; mov.b64 db, {%130,%131}; setp.ne.b32 p, %132, 0;\n"
    "wgmma.mma_async.sync.aligned.m64n256k16.f32.bf16.bf16 {%0,%1,%2,%3,%4,%5,%6,%7,%8,%9,%10,%11,%12,%13,%14,%15,%16,%17,%18,%19,%20,%21,%22,%23,%24,%25,%26,%27,%28,%29,%30,%31,%32,%33,%34,%35,%36,%37,%38,%39,%40,%41,%42,%43,%44,%45,%46,%47,%48,%49,%50,%51,%52,%53,%54,%55,%56,%57,%58,%59,%60,%61,%62,%63,%64,%65,%66,%67,%68,%69,%70,%71,%72,%73,%74,%75,%76,%77,%78,%79,%80,%81,%82,%83,%84,%85,%86,%87,%88,%89,%90,%91,%92,%93,%94,%95,%96,%97,%98,%99,%100,%101,%102,%103,%104,%105,%106,%107,%108,%109,%110,%111,%112,%113,%114,%115,%116,%117,%118,%119,%120,%121,%122,%123,%124,%125,%126,%127}, da, db, p, 1, 1, %133, %134; }"
    : "+f"(d[0]),"+f"(d[1]),"+f"(d[2]),"+f"(d[3]),"+f"(d[4]),"+f"(d[5]),"+f"(d[6]),"+f"(d[7]),"+f"(d[8]),"+f"(d[9]),"+f"(d[10]),"+f"(d[11]),"+f"(d[12]),"+f"(d[13]),"+f"(d[14]),"+f"(d[15]),"+f"(d[16]),"+f"(d[17]),"+f"(d[18]),"+f"(d[19]),"+f"(d[20]),"+f"(d[21]),"+f"(d[22]),"+f"(d[23]),"+f"(d[24]),"+f"(d[25]),"+f"(d[26]),"+f"(d[27]),"+f"(d[28]),"+f"(d[29]),"+f"(d[30]),"+f"(d[31]),"+f"(d[32]),"+f"(d[33]),"+f"(d[34]),"+f"(d[35]),"+f"(d[36]),"+f"(d[37]),"+f"(d[38]),"+f"(d[39]),"+f"(d[40]),"+f"(d[41]),"+f"(d[42]),"+f"(d[43]),"+f"(d[44]),"+f"(d[45]),"+f"(d[46]),"+f"(d[47]),"+f"(d[48]),"+f"(d[49]),"+f"(d[50]),"+f"(d[51]),"+f"(d[52]),"+f"(d[53]),"+f"(d[54]),"+f"(d[55]),"+f"(d[56]),"+f"(d[57]),"+f"(d[58]),"+f"(d[59]),"+f"(d[60]),"+f"(d[61]),"+f"(d[62]),"+f"(d[63]),"+f"(d[64]),"+f"(d[65]),"+f"(d[66]),"+f"(d[67]),"+f"(d[68]),"+f"(d[69]),"+f"(d[70]),"+f"(d[71]),"+f"(d[72]),"+f"(d[73]),"+f"(d[74]),"+f"(d[75]),"+f"(d[76]),"+f"(d[77]),"+f"(d[78]),"+f"(d[79]),"+f"(d[80]),"+f"(d[81]),"+f"(d[82]),"+f"(d[83]),"+f"(d[84]),"+f"(d[85]),"+f"(d[86]),"+f"(d[87]),"+f"(d[88]),"+f"(d[89]),"+f"(d[90]),"+f"(d[91]),"+f"(d[92]),"+f"(d[93]),"+f"(d[94]),"+f"(d[95]),"+f"(d[96]),"+f"(d[97]),"+f"(d[98]),"+f"(d[99]),"+f"(d[100]),"+f"(d[101]),"+f"(d[102]),"+f"(d[103]),"+f"(d[104]),"+f"(d[105]),"+f"(d[106]),"+f"(d[107]),"+f"(d[108]),"+f"(d[109]),"+f"(d[110]),"+f"(d[111]),"+f"(d[112]),"+f"(d[113]),"+f"(d[114]),"+f"(d[115]),"+f"(d[116]),"+f"(d[117]),"+f"(d[118]),"+f"(d[119]),"+f"(d[120]),"+f"(d[121]),"+f"(d[122]),"+f"(d[123]),"+f"(d[124]),"+f"(d[125]),"+f"(d[126]),"+f"(d[127])
    : "r"(alo), "r"(ahi), "r"(blo), "r"(bhi), "r"(sd), "n"(TA), "n"(TB)); }
  template<int TB> static __device__ __forceinline__ void rs(float* d, uint32_t a0, uint32_t a1, uint32_t a2, uint32_t a3, uint32_t blo, uint32_t bhi, int sd) {
  asm volatile("{ .reg .pred p; .reg .b64 db; mov.b64 db, {%132,%133}; setp.ne.b32 p, %135, 0;\n"
    "wgmma.mma_async.sync.aligned.m64n256k16.f32.bf16.bf16 {%0,%1,%2,%3,%4,%5,%6,%7,%8,%9,%10,%11,%12,%13,%14,%15,%16,%17,%18,%19,%20,%21,%22,%23,%24,%25,%26,%27,%28,%29,%30,%31,%32,%33,%34,%35,%36,%37,%38,%39,%40,%41,%42,%43,%44,%45,%46,%47,%48,%49,%50,%51,%52,%53,%54,%55,%56,%57,%58,%59,%60,%61,%62,%63,%64,%65,%66,%67,%68,%69,%70,%71,%72,%73,%74,%75,%76,%77,%78,%79,%80,%81,%82,%83,%84,%85,%86,%87,%88,%89,%90,%91,%92,%93,%94,%95,%96,%97,%98,%99,%100,%101,%102,%103,%104,%105,%106,%107,%108,%109,%110,%111,%112,%113,%114,%115,%116,%117,%118,%119,%120,%121,%122,%123,%124,%125,%126,%127}, {%128,%129,%130,%131}, db, p, 1, 1, %134; }"
    : "+f"(d[0]),"+f"(d[1]),"+f"(d[2]),"+f"(d[3]),"+f"(d[4]),"+f"(d[5]),"+f"(d[6]),"+f"(d[7]),"+f"(d[8]),"+f"(d[9]),"+f"(d[10]),"+f"(d[11]),"+f"(d[12]),"+f"(d[13]),"+f"(d[14]),"+f"(d[15]),"+f"(d[16]),"+f"(d[17]),"+f"(d[18]),"+f"(d[19]),"+f"(d[20]),"+f"(d[21]),"+f"(d[22]),"+f"(d[23]),"+f"(d[24]),"+f"(d[25]),"+f"(d[26]),"+f"(d[27]),"+f"(d[28]),"+f"(d[29]),"+f"(d[30]),"+f"(d[31]),"+f"(d[32]),"+f"(d[33]),"+f"(d[34]),"+f"(d[35]),"+f"(d[36]),"+f"(d[37]),"+f"(d[38]),"+f"(d[39]),"+f"(d[40]),"+f"(d[41]),"+f"(d[42]),"+f"(d[43]),"+f"(d[44]),"+f"(d[45]),"+f"(d[46]),"+f"(d[47]),"+f"(d[48]),"+f"(d[49]),"+f"(d[50]),"+f"(d[51]),"+f"(d[52]),"+f"(d[53]),"+f"(d[54]),"+f"(d[55]),"+f"(d[56]),"+f"(d[57]),"+f"(d[58]),"+f"(d[59]),"+f"(d[60]),"+f"(d[61]),"+f"(d[62]),"+f"(d[63]),"+f"(d[64]),"+f"(d[65]),"+f"(d[66]),"+f"(d[67]),"+f"(d[68]),"+f"(d[69]),"+f"(d[70]),"+f"(d[71]),"+f"(d[72]),"+f"(d[73]),"+f"(d[74]),"+f"(d[75]),"+f"(d[76]),"+f"(d[77]),"+f"(d[78]),"+f"(d[79]),"+f"(d[80]),"+f"(d[81]),"+f"(d[82]),"+f"(d[83]),"+f"(d[84]),"+f"(d[85]),"+f"(d[86]),"+f"(d[87]),"+f"(d[88]),"+f"(d[89]),"+f"(d[90]),"+f"(d[91]),"+f"(d[92]),"+f"(d[93]),"+f"(d[94]),"+f"(d[95]),"+f"(d[96]),"+f"(d[97]),"+f"(d[98]),"+f"(d[99]),"+f"(d[100]),"+f"(d[101]),"+f"(d[102]),"+f"(d[103]),"+f"(d[104]),"+f"(d[105]),"+f"(d[106]),"+f"(d[107]),"+f"(d[108]),"+f"(d[109]),"+f"(d[110]),"+f"(d[111]),"+f"(d[112]),"+f"(d[113]),"+f"(d[114]),"+f"(d[115]),"+f"(d[116]),"+f"(d[117]),"+f"(d[118]),"+f"(d[119]),"+f"(d[120]),"+f"(d[121]),"+f"(d[122]),"+f"(d[123]),"+f"(d[124]),"+f"(d[125]),"+f"(d[126]),"+f"(d[127])
    : "r"(a0), "r"(a1), "r"(a2), "r"(a3), "r"(blo), "r"(bhi), "n"(TB), "r"(sd)); }
};

template<int T> struct ConvR {
    static __device__ __forceinline__ void run(float* acc, const uint32_t* a, uint32_t db) {
        WG<256 - 16 * T>::template rs<0>(acc, a[4 * T], a[4 * T + 1], a[4 * T + 2], a[4 * T + 3], db + T * 16, dhi(128, 0), T != 0);
        ConvR<T + 1>::run(acc, a, db);
    }
};
template<> struct ConvR<16> { static __device__ __forceinline__ void run(float*, const uint32_t*, uint32_t) {} };

template<int O2> __device__ __forceinline__ bool check_tile(uint32_t a, uint32_t tag) {
    uint32_t bad;
    asm("{ .reg .b32 x, y; lop3.b32 x, %1, %2, %5, 0x7e; lop3.b32 y, %3, %4, %5, 0x7e; lop3.b32 %0, x, y, 1, 0xa8; }" : "=r"(bad) : "r"(lds32(a)), "r"(lds32(a + 128)), "r"(lds32(a + O2)), "r"(lds32(a + O2 + 128)), "r"(tag));
    return __any_sync(~0u, bad);
}
template<int N, int O1, int O2> __device__ __forceinline__ void repair_tile(uint32_t a, const char* g, uint32_t tag) {
    asm volatile("{\n .reg .pred p, q; .reg .b32 i, n, u, t, x, y, z, w; .reg .b64 ga, lo, hi; .reg .b128 v; mov.u32 i, 0; mov.u32 n, 0;\n"
                 "LAB_RP:\n and.b32 t, i, 1; mul.lo.u32 u, t, %4; shr.u32 t, i, 1; mad.lo.u32 u, t, %3, u; add.u32 t, u, %0; and.b32 u, t, 0xfffffff0; cvt.u64.u32 ga, u; add.u64 ga, ga, %1;\n"
                 " ld.relaxed.gpu.global.b128 v, [ga]; mov.b128 {lo, hi}, v; mov.b64 {x, y}, lo; mov.b64 {z, w}, hi; st.shared.v4.b32 [u], {x, y, z, w}; ld.volatile.shared.b32 t, [t];\n"
                 " xor.b32 t, t, %2; and.b32 t, t, 1; setp.ne.u32 p, t, 0; vote.sync.any.pred p, p, 0xffffffff; add.u32 n, n, 1; setp.lt.and.u32 p, n, 20000, p; @!p add.u32 i, i, 1;\n"
                 " setp.lt.u32 q, i, %5;\n @q bra.uni LAB_RP;\n fence.proxy.async.shared::cta;\n }" :: "r"(a), "l"(g), "r"(tag), "n"(O2), "n"(O1), "n"(N) : "memory");
    __syncwarp();
}
template<int P> __device__ __forceinline__ void hh_store(const uint32_t* hq, char* dst) { const uint32_t* o = hq + 4 * P; stg_v4(dst + (P >> 2) * 16384 + ((P >> 1) & 1) * 512 + (P & 1) * 1024, o[0], o[1], o[2], o[3]); }
template<int P, bool ST = true> __device__ __forceinline__ void ffn_epi(const float* g, const float* u, float rq0, float rq1, uint32_t* hq, char* dst, uint32_t tag) {
    const float rq = (P & 1) ? rq1 : rq0;
    uint32_t* o = hq + 4 * P;
    #pragma unroll
    for (int b = 0; b < 4; b++) { const int i = 16 * (P >> 1) + 4 * b + 2 * (P & 1); o[b] = hmul2(pack2relu(g[i], g[i + 1]), pack2(u[i] * rq, u[i + 1] * rq)); }
    o[2 * (P & 1) + ((P >> 1) & 1)] = tagbit(o[2 * (P & 1) + ((P >> 1) & 1)], tag);
    if (ST) hh_store<P>(hq, dst); else asm volatile("" : "+r"(o[0]), "+r"(o[1]), "+r"(o[2]), "+r"(o[3]));
}
__device__ __forceinline__ uint32_t tagged(float x, uint32_t tag) { return (__float_as_uint(x) & ~7u) | (tag & 7u); }
__device__ __forceinline__ uint32_t split2(float x) { const float h = bfround(x); return pack2(h, x - h); }
__device__ __forceinline__ void yield() { asm volatile("pmevent 1;" ::: "memory"); }
__device__ __forceinline__ void vfma(float& d, float a, float b) { asm volatile("fma.rn.f32 %0, %1, %2, %0;" : "+f"(d) : "f"(a), "f"(b)); }
__device__ __forceinline__ void vadd(float& d, float a) { asm volatile("add.f32 %0, %0, %1;" : "+f"(d) : "f"(a)); }
template<int I, int N, typename F> __device__ __forceinline__ void static_for(F&& f) {
    if constexpr (I < N) { f(std::integral_constant<int, I>{}); static_for<I + 1, N>(f); }
}

__device__ __forceinline__ int mod_col(int G) {
    const int s4 = (G >> 1) & 3;
    return G < 32 ? (s4 + (s4 == 3)) * 640 + (G >> 3) * 128 + (G & 1) * 64 : G < 34 ? 3072 + (G & 1) * 64 : G < 44 ? 1920 + (G - 34) * 64 :
           G < 50 ? ((G - 44) >> 1) * 640 + 512 + (G & 1) * 64 : 3200 + (G - 50) * 64;
}
__device__ __forceinline__ uint32_t silu2(uint32_t w) {
    const float a0 = bflo(w), a1 = bfhi(w);
    return pack2(__fdividef(a0, 1.f + __expf(-a0)), __fdividef(a1, 1.f + __expf(-a1)));
}

struct Maps { CUtensorMap k, v, q, o1, w[4]  , wd, wn, wm, out, ou2; };
struct Ptrs { const char *k, *v, *ssm, *shift, *ssmD, *c, *Wg, *Wu, *Wd; char *scr;
    Sched s;
    uint32_t zero[8];
};

__global__ void __cluster_dims__(2, 1, 1) __launch_bounds__(384, 1)
fused_kernel(const __grid_constant__ Ptrs P, const __grid_constant__ Maps M) {
    extern __shared__ __align__(1024) char smraw[];
    GSTAMPIF(threadIdx.x == 0, 63);
    uint32_t clk0;
    asm volatile("mov.u32 %0, %%clock;" : "=r"(clk0));
    const uint32_t sb = smem_u32(smraw);
    const int tid = threadIdx.x, lane = tid & 31;
    uint32_t tpc;
    asm("mov.u32 %0, %%smid;" : "=r"(tpc));
    tpc >>= 1;
    const int b = 2 * (tpc >= 62 ? tpc - 62 : tpc + 4) + (blockIdx.x & 1);
    const int warp = __shfl_sync(~0u, tid >> 5, 0);
    #define BAR(i) (sb + BARS + 8 * (i))
    #define CNT(i) ((uint32_t*)paddv(P.scr, (i) * 128))
    if (tid == 288) { pf_map(&M.k); pf_map(&M.v); }
    uint32_t epoch = 0;
    if (tid < 256) {
        asm volatile("ld.relaxed.gpu.global.u32 %0, [%1];" : "=r"(epoch) : "l"(CNT(C_ZO)) : "memory");
        if (tid < NPF && b < 128) asm volatile("prefetch.global.L2 [%0];" :: "l"(padd((tid & 32) ? P.v : P.k, (b * 16 + (lane >> 1)) * 1280 + (lane & 1) * 128 + (tid >> 6) * 256)) : "memory");
    }
    const int rank = b & 1, cl = b >> 1, cu = cl - 36, cv = (cu * 37) >> 8;
    const int gpc = cl < 4 ? 0 : cl < 36 ? (cl - 4) & 7 : 1 + cu - 7 * cv, pj = cl < 4 ? 4 + cl : cl < 36 ? (cl - 4) >> 3 : 4 + cv;
    const int sg = (0x73125460 >> (4 * gpc)) & 7;
    const int cg = 2 * (sg >> 2) + rank, tb = 8 * (sg & 3) + pj, bc = 32 * cg + tb;
    const int js = (sg & 4) + (pj & 3), tile = 4 * (sg & 3) + 2 * (pj >> 2) + rank;
    const int kh = js >> 2, dq = js & 3;
    auto load_kv = [&](int r) {
        tma3d(sb + kv_at(r), &M.k, r * 128 + cg * 32, 247 - 8 * tb, 0, BAR(B_KV + r));
        tma3d(sb + kv_at(r) + 4608, &M.v, r * 128 + cg * 32, 248 - 8 * tb, 0, BAR(B_KV + r));
    };
    auto load_h = [&](int r) { bulk_g2s(sb + 16 + h_at(r), padd(P.ssm, (bc + 128 * r) * 4096), 4096, BAR(B_H + r)); };
    auto t_task = [&](int n, int t7, uint32_t tag) {
        const int blk = t7 & 7, ch = 128 * n + 32 * cg + 2 * (t7 >> 3);
        uint32_t ka[8], sa = sb + SHT + ch * 8;
        #pragma unroll
        for (int i = 0; i < 4; i++) { ka[i] = (sb + kv_at(n) + blk * 64 + (t7 >> 3) * 4) ^ ((blk * 8 + i * 8) & 0x30); ka[i + 4] = ka[i] ^ 0x20; }
        char* dst = SC(kvT, ch * 4096 + (8 * tb + 7 - blk) * 16);
        #pragma unroll
        for (int i = 0; i < 8; i++) asm volatile("" : "+r"(ka[i]));
        asm volatile("" : "+r"(sa), "+l"(dst));
        mbar_wait(BAR(B_KV + n), 0);
        STAMPIF(t7 < 32, 195 + n);
        const uint4 sw = lds128(sa);
        uint32_t kr[11], o[8];
        #pragma unroll
        for (int i = 0; i < 11; i++) { const int row = i < 3 ? 9 * (i + 5) : 9 * (i - 3) + 1; kr[i] = lds32(ka[row & 7] + row * 64); }
        #pragma unroll
        for (int i = 0; i < 8; i++) o[i] = lds32(ka[0] + 4608 + i * 512);
        const uint32_t w0 = prmt(sw.x, sw.z, 0x5410), w1 = prmt(sw.x, sw.z, 0x7632), w2 = prmt(sw.y, sw.w, 0x5410), w3 = prmt(sw.y, sw.w, 0x7632);
        #pragma unroll
        for (int i = 0; i < 8; i++) o[i] = hmul2(o[i], hfma2(kr[i + 3], w0, hfma2(kr[i + 2], w1, hfma2(kr[i + 1], w2, hmul2(kr[i], w3)))));
        stg_tag2<4096>(dst, prmt(o[7], o[6], 0x5410), prmt(o[5], o[4], 0x5410), prmt(o[3], o[2], 0x5410), prmt(o[1], o[0], 0x5410),
                       prmt(o[7], o[6], 0x7632), prmt(o[5], o[4], 0x7632), prmt(o[3], o[2], 0x7632), prmt(o[1], o[0], 0x7632), tag);
    };
    if (b < 128 && warp == 9) {
        if (elect()) {
            mbar_init(BAR(B_KV), 1);
            fence_async_smem();
            mbar_expect(BAR(B_KV), KVP + 5120 + 1280);
            bulk_g2s(sb + SHT, P.shift, 5120, BAR(B_KV));
            bulk_g2s(sb + DS, P.ssmD, 1280, BAR(B_KV));
            load_kv(0);
            #pragma unroll
            for (int i = 1; i < B_XF; i++) mbar_init(BAR(i), 1);
            mbar_init(BAR(B_IN), 1);
            fence_async_smem();
        }
        __syncwarp();
    }
    const int kind = (lane * 13) >> 7, pr = (lane >> 1) - 5 * kind;
    const uint32_t* cp = nullptr;
    if (b < 128 && warp == 8) {
        const uint32_t base = (C_KV + (bc >> 5)) | (C_Y + cg) << 8 | (C_Z + tile) << 16 | (C_HH - 256 + tile * 2 + kh) << 24;
        cp = CNT((lane & 1) * 32 + ((base >> (8 * kind)) & 255) + (pr << (kind == 2 ? 6 : 2)) + (lane >= 30) * 256);
        asm volatile("cp.async.cg.shared.global [%0], [%1], 16;" :: "r"(sb + PS + lane * 16), "l"(cp) : "memory");
        sts32(sb + PRE + lane * 4, 0);
    }
    if (b >= 128) {
        if (tid == 256) { _Pragma("unroll") for (int i = 0; i < 16; i++) mbar_init(BAR(i), i < 8 ? 1 : 4); fence_async_smem(); }
        __syncthreads();
        if (warp >= 8) {
            if (elect()) {
                pf_map(&M.wm);
                wait_clock(clk0, P.s.d_sp + (warp - 8) * P.s.g_sp);
                _Pragma("unroll 1") for (int i = 0; i < 15; i++) {
                    const int col = mod_col(4 * i + b - 128), s = (i & 1) * 4 + warp - 8;
                    mbar_wait(BAR(8 + s), ~(i >> 1) & 1);
                    mbar_expect(BAR(s), 20480);
                    tma2d(sb + s * 20480, &M.wm, col, (warp - 8) * 160, BAR(s));
                    if (i == 0) pause(4 * P.s.g_sp);
                }
            }
        } else {
            const int wg = warp >> 2;
            sts32(sb + 204800 + tid * 4, silu2(__ldg((const uint32_t*)P.c + tid)));
            if (tid < 64) sts32(sb + 205824 + tid * 4, silu2(__ldg((const uint32_t*)P.c + 256 + tid)));
            fence_async_smem();
            bar_sync(1, 256);
            epoch = (epoch >> 7) + 1;
            _Pragma("unroll 1") for (int i = wg; i < 15; i += 2) {
                float acc[8];
                char* mp = SC(mod, (mod_col(4 * i + b - 128) + (warp & 3) * 16 + (lane >> 2)) * 4);
                _Pragma("unroll 1") for (int j = 0; j < 4; j++) {
                    const int s = wg * 4 + j;
                    const uint32_t da = dlo(sb + s * 20480, 16), db = dlo(sb + 204800 + j * 320, 16);
                    mbar_wait(BAR(s), (i >> 1) & 1);
                    wg_fence();
                    #pragma unroll
                    for (int ks = 0; ks < 10; ks++) WG<8>::ss<1, 0>(acc + 4 * (ks & 1), da + ks * 128, dhi(1024, 1), db + ks * 2, dhi(128, 0), ks > 1 || j != 0);
                    wg_commit();
                    wg_wait<0>();
                    pin<8>(acc);
                    mbar_arrive_if(BAR(8 + s), lane == 0);
                }
                if ((lane & 3) == 0) asm volatile("st.relaxed.gpu.global.u32 [%0], %1; st.relaxed.gpu.global.u32 [%0+32], %2;" :: "l"(mp), "r"(tagged(acc[0] + acc[4], epoch)), "r"(tagged(acc[2] + acc[6], epoch)) : "memory");
                STAMPIF(warp == 4, 110 + (i >> 1));
                STAMPIF(warp == 0 && i == 12, 117);
            }
        }
        PROF_EXIT();
        return;
    }

    if (warp >= 10) {
        if (elect()) {
            if (warp == 10) { _Pragma("unroll") for (int i = B_XF; i < 47; i++) mbar_init(BAR(i), bar_count(i)); }
            else { _Pragma("unroll") for (int i = 47; i < NBARS; i++) mbar_init(BAR(i), bar_count(i)); }
            asm volatile("fence.mbarrier_init.release.cluster;" ::: "memory");
        }
        if (lane < 24) sts128(sb + PB - (warp & 1) * 32768 + (lane & 3) * PP + 4096 + (lane >> 2) * 16, 0, 0, 0, 0);
        if (lane < 12) sts128(sb + (lane < 5 ? h_at(lane) : lane == 5 ? HO0 : lane == 6 ? HO1 : x_at(lane - 7) + 4096), 0, 0, 0, 0);
        fence_async_smem();
    }
    if (warp == 9) bar_arrive(0, 384); else bar_sync(0, 384);
    STAMPIF(warp == 0, 192);
    asm volatile("barrier.cluster.arrive.relaxed.aligned;" ::: "memory");
    STAMPIF(warp == 0, 6);

    if (warp < 8) {
        const int wg = warp >> 2, w = warp & 3;
        const int q = lane & 3, rr = lane >> 2;
        const bool l0 = lane == 0;
        asm volatile("setmaxnreg.inc.sync.aligned.u32 224;");
        asm volatile("barrier.cluster.wait.aligned;" ::: "memory");
        #define ln (t7 & 31)
        auto reduce = [&](int r, int t7, uint32_t tg, auto&& first) {
            char* yp = SC(yB, ((r * 4 + (bc >> 5)) * 32 + (t7 >> 3)) * 4096 + (bc & 31) * 128 + (((t7 & 7) ^ ((bc & 1) << 2)) << 4));
            void* hp = CNT(C_Y + 4 * r + (bc >> 5) + 32 * (ln & 1));
            asm volatile("" : "+l"(yp));
            first();
            bar_sync(5 + wg, 128);
            uint4 p[2][4];
            #pragma unroll
            for (int h = 0; h < 2; h++)
            #pragma unroll
            for (int k = 0; k < 4; k++) p[h][k] = lds128(sb + PB - wg * 32768 + (t7 + 128 * h) * 16 + k * (PP + 32));
            uint32_t y[8];
            #pragma unroll
            for (int j = 0; j < 8; j++) y[j] = hadd2((&p[j >> 2][0].x)[j & 3], hadd2((&p[j >> 2][1].x)[j & 3], hadd2((&p[j >> 2][2].x)[j & 3], (&p[j >> 2][3].x)[j & 3])));
            stg_tag2<65536>(yp, y[0], y[1], y[2], y[3], y[4], y[5], y[6], y[7], tg);
            if (w) {
                bar_arrive(8 + wg, 128);
            } else {
                bar_sync(8 + wg, 128);
                LATE(hint_cnt(hp, ln < 2));
                pre_add(sb + PRE + 44 + r * 8 + (ln & 1) * 20, ln < 1 + (r >= 3));
                STAMP(10 + r * 3);
            }
        };
        {
        int t7 = __shfl_sync(~0u, tid & 127, lane);
        auto ff_arrive = [&](int i, bool p) {
            uint32_t a;
            asm("mapa.shared::cluster.u32 %0, %1, %2;" : "=r"(a) : "r"(BAR(B_FF + i)), "r"(rank ^ (t7 & 1)));
            mbar_arrive_remote_if(a, p && ln < 2);
        };
        uint32_t fa[64];
        auto odd_copy = [&](int n) {
            const uint32_t src = sb + 16 + h_at(n) + t7 * 16, dst = sb + 16 + (wg ? HO1 : HO0) + t7 * 16;
            uint32_t dr;
            asm volatile("ld.shared.u16 %0, [%1];" : "=r"(dr) : "r"(sb + DS + (bc + 128 * n) * 2) : "memory");
            mbar_wait(BAR(B_H + n), 0);
            STAMPIF(w == 0, 140 + n);
            uint4 v = lds128(src); const uint4 u = lds128(src + 2048);
            const uint32_t pv = lds32(src - 4), pu = lds32(src + 2044);
            if (t7 == 0) { v.x = hadd2(v.x, dr); sts32(src, v.x); }
            sts128(dst, prmt(pv, v.x, 0x5432), prmt(v.x, v.y, 0x5432), prmt(v.y, v.z, 0x5432), prmt(v.z, v.w, 0x5432));
            sts128(dst + 2048, prmt(pu, u.x, 0x5432), prmt(u.x, u.y, 0x5432), prmt(u.y, u.z, 0x5432), prmt(u.z, u.w, 0x5432));
        };
        auto frags = [&](int n, auto I0, auto I1) {
            const uint32_t a = sb + 16 + ((ln & 4) ? (wg ? HO1 : HO0) : h_at(n)) + 32 * w + 4 * (ln & 3) - 4 * (ln >> 3);
            #pragma unroll
            for (int i = I0.value; i < I1.value; i++) fa[i] = lds32(a + (i >> 2) * 256 + (i & 1) * 128 + (i & 2) * 8);
        };
        using I0 = std::integral_constant<int, 0>; using IA = std::integral_constant<int, FA>; using I64 = std::integral_constant<int, 64>;
        if (wg) mbar_wait(BAR(B_KV), 0);
        uint32_t list = P.s.wl[wg];
        _Pragma("unroll 1") for (int r = wg; r < 5; r += 2) {
            _Pragma("unroll 1") for (; list; list >>= 4) {
                const int n = (list & 15) - 1;
                t7 |= list >> 31;
                if (n < 5) {
                    void* hp = CNT(C_KV + 4 * n + cg + 32 * (ln & 1));
                    EARLY(mbar_wait(BAR(B_CR), 0); hint_cnt(hp, t7 < 2));
                    t_task(n, t7, (epoch >> 7) + 1 + (list >> 31));
                    if (w) bar_arrive(10 + n, 128);
                    else {
                        if (n < 2) mbar_wait(BAR(B_CR), 0);
                        bar_sync(10 + n, 128);
                        LATE(hint_cnt(hp, ln < 2));
                        pre_add(sb + PRE + n * 8 + 4, ln == 0);
                        ff_arrive(n >= 3, true);
                        STAMP(n);
                    }
                } else {
                    odd_copy(wg);
                    bar_sync(5 + wg, 128);
                    frags(wg, I0{}, I64{});
                    STAMPIF(w == 0, 145 + r);
                }
            }
            float acc[128];
            const uint32_t xa = sb + x_at(r), pb = sb + PB - wg * 32768, nx = BAR(r == 4 ? B_GO : B_XF + 1 + r);
            uint32_t db = dlo(xa, 16);
            list = P.s.wl[r + 2];
            t7 |= list >> 31;
            const uint32_t tg = (epoch >> 7) + 1 + (list >> 31);
            if (r == 4) ff_arrive(2, true); else pre_add(sb + PRE + 80, ln == 0 && r >= 2);
            asm volatile("" : "+r"(db));
            EARLY(hint_cnt(CNT(C_Y + 4 * r + (bc >> 5) + 32 * (ln & 1)), t7 < 2));
            mbar_wait(BAR(B_XF + r), 0);
            KSTAMP(w == 0, 8 + r * 3); GSTAMPIF(w == 0 && r == 0, 106);
            _Pragma("unroll 1") for (int tries = 0;; tries++) {
                wg_fence();
                ConvR<0>::run(acc, fa, db);
                wg_commit();
                mbar_arrive_if(nx, ln == 0 && !tries);
                uint32_t bad = (lds32(xa + t7 * 16) ^ tg) | (lds32(xa + t7 * 16 + 2048) ^ tg);
                if (r < 3 && !tries) odd_copy(r + 2);
                wg_wait<0>();
                pin<128>(acc);
                asm volatile("{ .reg .pred p; setp.ne.b32 p, %1, 0; barrier.red.or.pred.aligned p, %2, 128, p; selp.u32 %0, 1, 0, p; }" : "=r"(bad) : "r"(bad & 1), "r"(5 + wg) : "memory");
                if (!bad || tries) break;
                repair_tile<2, 2048, 0>(xa + t7 * 16, SC(kvT, (bc + 128 * r) * 4096) - xa, tg);
                bar_sync(5 + wg, 128);
                STAMP(121);
            }
            STAMPIF(w == 0, 9 + r * 3);
            t7 |= list >> 30;
            const uint32_t pw = pb + w * PP + ln * 16;
            #pragma unroll
            for (int g = 0; g < 8; g++) {
                uint32_t o[4];
                #pragma unroll
                for (int l = 0; l < 4; l++) { const int i = 4 * g + l;
                    o[l] = i < 31 ? pack2(acc[4 * i] + acc[4 * i + 6], acc[4 * i + 1] + acc[4 * i + 7]) : pack2(acc[4 * i], acc[4 * i + 1]); }
                asm volatile("stmatrix.sync.aligned.m8n8.x4.trans.shared.b16 [%0], {%1,%2,%3,%4};" :: "r"(pw + g * 512), "r"(o[0]), "r"(o[1]), "r"(o[2]), "r"(o[3]) : "memory");
            }
            if (RD4 && r == 4) break;
            reduce(r, t7, tg, [&]() { if (FA && r < 3) frags(r + 2, I0{}, IA{}); });
            if (r < 3) { frags(r + 2, IA{}, I64{}); STAMPIF(w == 0, 147 + r); }
        }
        #undef ln
        }
        float acc1[128];
        const uint32_t tag = (epoch >> 7) + 1;
        uint32_t g2e;
        asm("mapa.shared::cluster.u32 %0, %1, %2;" : "=r"(g2e) : "r"(BAR(lane == 2 ? B_HE - 2 : B_G2E)), "r"(rank ^ (lane & 1)));
        const bool l01 = lane < 2;
        const uint32_t wre = g2e - 8 * (B_G2E - B_WE);
        uint32_t p1a = dlo(sb + wg * 8192, 2048), p1s = 0;
        uint32_t va = sb + (w >> 1) * 2048 + (lane >> 3) * 516 + (lane & 1) * 64 + (lane & 2) * 128 + ((((w << 1) ^ lane) & 2) + ((lane >> 2) & 1)) * 16;
        uint32_t tw[4];
        auto a_ready = [&](int kb) {
            mbar_wait(BAR(B_AF) + kb * 8, 0);
            #pragma unroll
            for (int i = 0; i < 4; i++) tw[i] = lds32(va + (i & 1) * 128 + (i >> 1) * 4096);
        };
        auto a_check = [&]() {
            uint32_t bad;
            asm("{ .reg .b32 x, y; lop3.b32 x, %1, %2, %5, 0x7e; lop3.b32 y, %3, %4, %5, 0x7e; lop3.b32 %0, x, y, 1, 0xa8; }" : "=r"(bad) : "r"(tw[0]), "r"(tw[1]), "r"(tw[2]), "r"(tw[3]), "r"(tag));
            if (__builtin_expect(__any_sync(~0u, bad), 0)) { repair_tile<4, 128, 4096>(va, SC(z, tile * 163840) - sb, tag); STAMP(118); }
            va += 16384;
        };
        if (wg) {
            mbar_wait(BAR(B_AF), 0);
            if (__builtin_expect(check_tile<4096>(va, tag) | check_tile<4096>(va + 8192, tag), 0)) repair_tile<8, 128, 4096>(va, SC(z, tile * 163840) - sb, tag);
            mbar_arrive_if(BAR(B_GO), l0);
        }
        va += 16384 + wg * 8192;
        mbar_wait(BAR(B_GO), 0);
        KSTAMP(w == 0, 24 + wg);
        GSTAMPIF(warp == 0, 107);
        auto pass1 = [&](int k0, int k1, auto&& mid) {
            _Pragma("unroll 1") for (int kb = k0; kb < k1; kb++) {
                const uint32_t so = p1s & 16, db = dlo(sb + WR, 4096) + so * 128;
                #pragma unroll
                for (int h = 0; h < 2; h++) {
                    mbar_wait(BAR(B_WF + h) + so, p1s >> 31);
                    STAMPIF(warp == PW, 64 + 2 * kb + h);
                    wg_fence();
                    WG<256>::ss<1, 1>(acc1, p1a + h * 256, dhi(512, 2), db + h * 1024, dhi(1024, 1), (h || k0) ? 1 : kb);
                    mid(h, kb);
                    WG<256>::ss<1, 1>(acc1, p1a + h * 256 + 64, dhi(512, 2), db + h * 1024 + 128, dhi(1024, 1), 1);
                    wg_commit();
                    wg_wait<1>();
                    mbar_arrive_remote_if(wre + (h ? so : (so ^ 16) + 8), l01 && (kb + h) > 0);
                    if (h && k0 < 9) a_check();
                }
                p1a += 1024; p1s = (p1s ^ 16) + (so << 27);
            }
        };
        uint32_t ax[4];
        float acc2[64];
        float rq0, rq1;
        uint32_t m0, m1, d0, d1, stale;
        auto next_a = [&](int h, int kb) { if (RD4 && h == ((RD4 - 1) & 1) && kb == ((RD4 - 1) >> 1) && !wg) reduce(4, tid, tag, []() {}); if (h) a_ready(kb + 1); };
        pass1(0, KB_UT, next_a);
        {
            float au[8];
            const uint32_t ua = dlo(sb + UST + wg * 16384, 16), ub = dlo(sb + CS_TAB, 32);
            mbar_wait(BAR(B_UF), 0);
            KSTAMP(warp == 0, 33);
            wg_fence();
            #pragma unroll
            for (int ks = 0; ks < 8; ks++) WG<8>::ss<1, 0>(au + 4 * (ks & 1), ua + ks * 128, dhi(1024, 1), ub + ks * 4, dhi(128, 0), ks > 1);
            wg_commit();
            pass1(KB_UT, KB_UT + 1, [&](int h, int kb) { if (h) {
            pin<8>(au);
            pre_add(sb + PRE + 104, l0);
            const int t3 = (tile * 11) >> 5, cn = 2 * (tile - 3 * t3) + wg;
            asm volatile("{ .reg .pred p; .reg .b64 x; setp.eq.b32 p, %5, 0; mov.b64 x, {%1, %2}; @p st.relaxed.gpu.global.b64 [%0], x; mov.b64 x, {%3, %4}; @p st.relaxed.gpu.global.b64 [%0+64], x; }"
                         :: "l"(SC(ut, (t3 * 3072 + (cn >= 3) * 1344 + js * 192 + cn * 64 + w * 16 + rr) * 8)), "r"(tagged(au[0] + au[4], tag)), "f"(au[1] + au[5]), "r"(tagged(au[2] + au[6], tag)), "f"(au[3] + au[7]), "r"(q | (tile == 15)) : "memory");
            mbar_arrive_if(BAR(B_UD), l0);
            STAMPIF(warp == 0, 60);
            a_ready(kb + 1);
            } });
        }
        unsigned long long sv[8] = {};
        const char* s2p = SC(st2, ((tile * 2 + wg) * 256 + 63 - 16 * (rr >> 1) - (rr & 1) - 4 * w) * 8);
        auto st_load = [&](bool p) {
            #pragma unroll
            for (int i = 0; i < 8; i++)
                asm volatile("{ .reg .pred p; setp.ne.b32 p, %2, 0; @p ld.relaxed.gpu.global.b64 %0, [%1]; }" : "+l"(sv[i]) : "l"(s2p + (i & 3) * 512 - (i >> 2) * 16), "r"((int)p) : "memory");
        };
        auto st_row = [&](const unsigned long long* u, float& rq, uint32_t& m, uint32_t& d) {
            float2 v[4];
            #pragma unroll
            for (int i = 0; i < 4; i++) v[i] = make_float2(__uint_as_float((uint32_t)u[i]), __uint_as_float(u[i] >> 32));
            stale |= (__float_as_uint(v[0].x) ^ tag) | (__float_as_uint(v[1].x) ^ tag) | (__float_as_uint(v[2].x) ^ tag) | (__float_as_uint(v[3].x) ^ tag);
            const float mu = ((v[0].x + v[1].x) + (v[2].x + v[3].x)) * (1.f / D_), ve = fmaxf(((v[0].y + v[1].y) + (v[2].y + v[3].y)) * (1.f / D_) - mu * mu, 0.f) + 1e-5f;
            asm("rsqrt.approx.ftz.f32 %0, %1;" : "=f"(rq) : "f"(ve));
            d = split2(ve * rq); m = split2(-mu); rq *= rq;
            asm volatile("" : "+r"(d), "+r"(m), "+f"(rq), "+r"(stale) :: "memory");
        };
        pass1(KB_UT + 1, 9, [&](int h, int kb) { if (h == 0) st_load(kb == 8); else a_ready(kb + 1); });
        stale = 0;
        pass1(9, 10, [&](int h, int) { if (h == 0) st_row(sv, rq0, m0, d0); else st_row(sv + 4, rq1, m1, d1); });
        _Pragma("unroll 1") for (int it = 0; it < 20000 && __any_sync(~0u, (stale & 7) != 0); it++) { stale = 0; st_load(true); st_row(sv, rq0, m0, d0); st_row(sv + 4, rq1, m1, d1); }
        {
            const uint32_t zm = q == 0 ? ~0u : q == 1 ? 0xffffu : 0u, sh = q ? 0x5454 : 0x5410, sl = sh + 0x2222;
            ax[0] = prmt(m0, d0, sh) & zm; ax[1] = prmt(m1, d1, sh) & zm; ax[2] = prmt(m0, d0, sl) & zm; ax[3] = prmt(m1, d1, sl) & zm;
            asm volatile("" : "+r"(ax[0]), "+r"(ax[1]), "+r"(ax[2]), "+r"(ax[3]) :: "memory");
        }
        {
            mbar_wait(BAR(B_T1), 0);
            wg_fence();
            WG<256>::rs<1>(acc1, ax[0], ax[1], ax[2], ax[3], dlo(sb + TAB1, 0), dhi(48, 0), 1);
            WG<128>::rs<1>(acc2, ax[0], ax[1], ax[2], ax[3], dlo(sb + TAB2, 0), dhi(48, 0), 0);
            wg_commit();
        }
        char* hdst = SC(hh, (tile * 24 + js * 3) * 16384 + wg * 8192 + w * 2048 + rr * 64 + ((q ^ (rr >> 1)) << 4));
        wg_wait<1>();
        mbar_arrive_remote_if(wre + 24, l01);
        KSTAMP(w == 0, 26 + wg);
        GSTAMPIF(warp == 0, 108);
        uint32_t hq[48];
        static_for<0, 10>([&](auto IT) {
            constexpr int it = IT.value;
            mbar_wait(BAR(w2_bar(it)), it < 4);
            STAMPIF(warp == 0, 84 + it);
            const uint32_t da = dlo(sb + it * 16384 + wg * 8192, 2048), db = dlo(sb + w2_at(it), 8192);
            wg_fence();
            static_for<0, 4>([&](auto KS) {
                constexpr int ks = KS.value;
                WG<128>::ss<1, 1>(acc2, da + (ks >> 1) * 256 + (ks & 1) * 64, dhi(512, 2), db + ks * 128, dhi(1024, 1), 1);
                if constexpr (ks == 0) {
                    wg_commit();
                    wg_wait<1>();
                    if (it == 0) pin<128>(acc1);
                    if ((it > 0 && it < 6) || it == 7) mbar_arrive_remote_if(wre + 8 * (it == 7 ? 1 : (it + 3) & 3), l01);
                    static_for<0, 6>([&](auto G) { if constexpr (((B2S >> (4 * G.value)) & 15) == it) mbar_arrive_remote_if(g2e + 8 * G.value, l01); });
                }
                static_for<0, 8>([&](auto PP_) {
                    constexpr int hs = (HPS >> (4 * PP_.value)) & 15;
                    if constexpr (PP_.value == 2 * it + ks && ks < 2) ffn_epi<7 - PP_.value, false>(acc1, acc1 + 64, rq0, rq1, hq, hdst, tag);
                    if constexpr (hs == 2 * it + ks && ks < 2) hh_store<7 - PP_.value>(hq, hdst);
                    if constexpr ((PP_.value & 3) == 3 && (hs >> 1) == it && ks == 3) { __syncwarp(); mbar_arrive_if(BAR(PP_.value == 3 ? B_HD : B_HD + 1), l0); }
                });
            });
            wg_commit();
        });
        KSTAMP(w == 0, 30 + wg);
        {
            float acc[80];
            auto release = [&](int n) { wg_commit(); wg_wait<1>(); mbar_arrive_remote_if(g2e + 8 * (n - 1), lane < 2 + (n > 2 && n < 6)); };
            auto own = [&](auto IT) {
                constexpr int it = IT.value, n = it == 2 ? 5 : it;
                mbar_wait(BAR(B_G2F + n), 0);
                STAMPIF(w == 0 && it == 0, 34 + wg);
                STAMPIF(w == 0 && wg == kh, 94 + n);
                const uint32_t db = dlo(sb + g2b_at(n), 2048);
                #pragma unroll
                for (int i = 0; i < 16; i++) asm volatile("" : "+r"(hq[16 * it + i]) :: "memory");
                wg_fence();
                #pragma unroll
                for (int ks = 0; ks < 4; ks++) {
                    const uint32_t* o = hq + 16 * it + 8 * (ks >> 1) + 2 * (ks & 1);
                    WG<160>::rs<1>(acc, o[0], o[4], o[1], o[5], db + (ks >> 1) * 640 + (ks & 1) * 64, dhi(512, 2), it != 0 || ks != 0);
                    if (it == 0 && ks == 1) {
                        wg_commit();
                        wg_wait<1>();
                        pin<64>(acc2);
                        mbar_arrive_if(BAR(B_S0), l0);
                        static_for<0, 6>([&](auto G) { if constexpr (((B2S >> (4 * G.value)) & 15) == 10) mbar_arrive_remote_if(g2e + 8 * G.value, l01); });
                        ffn_epi<0>(acc2, acc2 + 32, rq0, rq1, hq + 32, hdst + 32768, tag);
                        wg_fence();
                    }
                    if (it && ks == 0) release(n);
                    if (it == 1 && ks == 0) ffn_epi<2>(acc2, acc2 + 32, rq0, rq1, hq + 32, hdst + 32768, tag);
                    if (it == 1 && ks == 1) { ffn_epi<3>(acc2, acc2 + 32, rq0, rq1, hq + 32, hdst + 32768, tag); __syncwarp(); mbar_arrive_if(BAR(B_HD), l0); }
                }
                wg_commit();
                if (it == 0) ffn_epi<1>(acc2, acc2 + 32, rq0, rq1, hq + 32, hdst + 32768, tag);
            };
            auto block = [&](int it, auto&& mid) {
                const int g = it >= 6 ? it - 6 : it, ga = ((it >= 6 ? 0x325104 : 0x32500) >> (4 * g)) & 7;
                const uint32_t da = dlo(sb + G2A + ga * 16384 + wg * 8192, 16), db = dlo(sb + g2b_at(g), 2048);
                mbar_wait(BAR(B_G2F + g), it >= 6);
                STAMPIF(w == 0 && it == 12 - SG, 36 + (wg ^ kh));
                STAMPIF(w == 0 && wg == kh, 94 + it);
                wg_fence();
                #pragma unroll
                for (int ks = 0; ks < 4; ks++) {
                    WG<160>::ss<0, 1>(acc, da + (ks >> 1) * 32 + (ks & 1) * 2, dhi(1024, 2), db + (ks >> 1) * 640 + (ks & 1) * 64, dhi(512, 2), 1);
                    mid(ks);
                }
                wg_commit();
            };
            own(std::integral_constant<int, 0>{}); own(std::integral_constant<int, 1>{});
            _Pragma("unroll 1") for (int it = 2; it < 5; it++) block(it, [&](int ks) { if (ks == 0) release(it); });
            own(std::integral_constant<int, 2>{});
            #pragma unroll
            for (int it = 6; it < 12 - SG; it++) block(it, [&](int ks) { if (ks == 0 && it == 6) release(it); });
            uint32_t gw[20], oa[10];
            const uint32_t ost = sb + G2A + warp * 2048, odd = dq & 1;
            const int row = S_ - 128 * tile - 16 * warp - 16;
            auto prep = [&]() {
            mbar_wait(BAR(B_X1), 0);
            #pragma unroll
            for (int i = 0; i < 5; i++) { const uint4 g = lds128(sb + GBT + q * 80 + i * 16); gw[4 * i] = g.x; gw[4 * i + 1] = g.y; gw[4 * i + 2] = g.z; gw[4 * i + 3] = g.w; }
            #pragma unroll
            for (int i = 0; i < 20; i++) asm volatile("" : "+r"(gw[i]));
            const uint32_t orow = 15 - (lane & 15);
            #pragma unroll
            for (int i = 0; i < 10; i++) {
                const int j = i < 2 ? (odd ? 8 + i : i) : i - 2 * odd;
                oa[i] = j < 8 ? ost + (j >> 2) * 16384 + orow * 128 + (((2 * (j & 3) + (lane >> 4)) ^ (orow & 7)) << 4) : ost + 32768 + orow * 64 + (((2 * (j & 1) + (lane >> 4)) ^ ((orow >> 1) & 3)) << 4);
                asm volatile("" : "+r"(oa[i]));
            }
            };
            if (wg != kh) { prep(); bar_sync(7, 256); }
            #pragma unroll
            for (int it = 12 - SG; it < 12; it++) block(it, [&](int) {});
            if (wg == kh) { bar_arrive(7, 256); prep(); }
            wg_wait<0>();
            pin<80>(acc);
            KSTAMP(w == 0, 38 + (wg ^ kh));
            GSTAMPIF(w == 0 && wg == kh, 109);
            #pragma unroll
            for (int i = 0; i < 10; i++) {
                uint32_t o[4];
                #pragma unroll
                for (int j = 0; j < 4; j++) { const int n = 4 * i + j; o[j] = hmul2(pack2(acc[2 * n], acc[2 * n + 1]), gw[n >> 1]); }
                asm volatile("stmatrix.sync.aligned.m8n8.x4.shared.b16 [%0], {%1,%2,%3,%4};" :: "r"(oa[i]), "r"(o[0]), "r"(o[1]), "r"(o[2]), "r"(o[3]) : "memory");
                if (ESPLIT && i == 5) {
                    fence_async_smem();
                    __syncwarp();
                    if (elect()) tma2d_red(&M.out, ost, dq * 160 + 32 * odd, row);
                }
            }
            fence_async_smem();
            __syncwarp();
            STAMPIF(w == 0, 123 + (wg ^ kh));
            if (elect()) {
                if (!ESPLIT) tma2d_red(&M.out, ost, dq * 160 + 32 * odd, row);
                tma2d_red(&M.out, ost + 16384, dq * 160 + 32 * odd + 64, row);
                tma2d_red(&M.ou2, ost + 32768, dq * 160 + 128 - 128 * odd, row);
                asm volatile("cp.async.bulk.commit_group;\n cp.async.bulk.wait_group.read 0;" ::: "memory");
            }
            KSTAMP(w == 0, 42 + (wg ^ kh));
            GSTAMPIF(w == 0 && wg == kh, 47);
        }
        PROF_EXIT();
    } else {
        asm volatile("setmaxnreg.dec.sync.aligned.u32 56;");
        if (warp == 9) {
            auto pf_w = [&](int r) { pf_l2(padd(P.Wg, (128 * r + b) * 3072), 3072); pf_l2(padd(P.Wu, (128 * r + b) * 3072), 3072); };
            auto load_w = [&](int m) {
                mbar_expect(BAR(B_WF + (m & 3)), 16384);
                tma3d_mc(sb + WR + (m & 3) * 16384 + rank * 8192, &M.w[0] + rank, m * 32, js * 3, BAR(B_WF + (m & 3)));
            };
            if (elect()) {
                pf_map(&M.q);
                _Pragma("unroll 1") for (int i = 0; P.s.ld[i]; i++) {
                    const uint32_t e = P.s.ld[i], n = e & 15;
                    if (e & 192) mbar_wait(BAR(B_IN), 0);
                    if (e & 64) {
                        const int tl = tile - (tile == 15), t3 = (tl * 11) >> 5, cm = 2 * (tl - 3 * t3) + (n >> 1);
                        wait_clock(clk0, e >> 8);
                        mbar_wait(BAR(B_FF), 0);
                        tma3d(sb + UST + n * 8192, cm >= 3 ? &M.w[3] : &M.w[2], 0, t3 * 128 + (n & 1) * 64, js * 3 + cm - 3 * (cm >= 3), BAR(B_UF));
                    } else if (e & 128) { wait_clock(clk0, e >> 8); if (n & 2) mbar_wait(BAR(B_FF - 1 + n), 0); load_w(n);
                    } else if (e & 32) {
                        if (e & 16) { wait_clock(clk0, e >> 8); pf_w(n); }
                        else { mbar_expect(BAR(B_Q + n), 4096); wait_clock(clk0, e >> 8); tma4d(sb + QS + n * 4096, &M.q, n * 128 + cg * 32, 248 - 8 * tb, BAR(B_Q + n)); }
                    } else if (e & 16) { mbar_expect(BAR(B_H + n), 4096); wait_clock(clk0, e >> 8); load_h(n); }
                    else { mbar_expect(BAR(B_KV + n), KVP); wait_clock(clk0, e >> 8); load_kv(n); }
                }
                STAMP(126);
                _Pragma("unroll 1") for (int m = 4; m < 20; m++) {
                    mbar_wait(BAR(B_WE + (m & 3)), ~(m >> 2) & 1);
                    load_w(m);
                    if (m == 12) pf_l2(padd(P.Wd, b * 15360), 15360);
                }
                #pragma unroll
                for (int it = 0; it < 10; it++) {
                    if (it < 4 || !(it & 1)) mbar_wait(BAR(B_WE + (it < 4 ? it : (it >> 1) - 2)), it >= 4);
                    mbar_expect(BAR(w2_bar(it)), 16384);
                    tma3d_mc(sb + w2_at(it) + rank * 8192, &M.w[2] + rank, it * 64, js * 3 + 2, BAR(w2_bar(it)));
                }
                #pragma unroll
                for (int m = 0; m < 9; m++) mbar_expect(BAR(B_AF + m), 16384);
                const char* hp[3];
                #pragma unroll
                for (int m = 0; m < 3; m++) hp[m] = SC(hh, (tile * 24 + (kh * 4 + m + (m >= dq)) * 3) * 16384);
                const uint32_t* fl = CNT(C_HH + tile * 2 + kh);
                const uint32_t target = lds32(sb + HT);
                sts128(sb + TAB1, target - 1, target - 1, target - 1, 0); sts128(sb + TAB1 + 16, target - 1, target - 1, target - 1, 0);
                #pragma unroll
                for (int c = 0; c < 3; c++) {
                    #pragma unroll
                    for (int m = 0; m < 3; m++) {
                        if (c != 1 || m == 0) wait_dual(fl, sb + TAB1, 4 * c, target, BAR(c == 0 ? B_WE + ((m + 3) & 3) : c == 1 ? B_S0 : B_HE + m), c + m == 0);
                        STAMPIF(m == 0, 170 + c); STAMPIF(m == 2, 173 + c);
                        bulk_g2s(sb + G2A + ((c & 1) ? (m ? m - 1 : 4) : m ? m + 1 : 5) * 16384, hp[m] + (c ^ (c < 2)) * 16384, 16384, BAR(B_AF + 3 * c + m));
                    }
                }
                asm volatile("cp.async.wait_all;" ::: "memory");
            }
            PROF_EXIT();
            return;
        }
        if (warp == 8) {
            const int r = pr;
            const char* src = kind == 0 ? SC(kvT, (bc + 128 * r) * 4096) : kind == 1 ? SC(yB, ((r * 4 + cg) * 32 + tb) * 4096) : SC(z, (tile * 10 + lane - 20) * 16384);
            const uint32_t dst = sb + (kind == 0 ? x_at(r) : kind == 1 ? YS + (r - 3 * (r >= 3)) * 4096 : (lane - 20) * 16384);
            const uint32_t bytes = kind == 2 ? 16384 : 4096, full = BAR(kind == 2 ? B_AF - 20 + lane : B_XF + (lane >> 1)), pre = sb + PRE + (lane >> 1) * 8, slot = sb + PS + lane * 16;
            uint32_t need = lane >= 30 ? ~0u : lane < 16 ? 0 : (0x1811822 >> (2 * (lane & 14))) & 15;
            const uint32_t lbit = __shfl_sync(~0u, (kind == 2 || (kind < 2 && !(lane & 1))) ? 1u << lane : 0u, lane), pbit = __shfl_sync(~0u, 3u << (lane & 30), lane);
            uint32_t todo = 0x15555555, it = 0;
            if (lbit) mbar_expect(full, bytes);
            asm volatile("cp.async.wait_all;" ::: "memory");
            const uint32_t goal = (lds32(slot) | 127) + 1;
            if (lane == 31) sts32(sb + HT, goal);
            __syncwarp();
            mbar_arrive_if(BAR(B_CR), lane == 0);
            STAMP(5);
            if (lane == 0) mbar_expect(BAR(B_UF), 32768);
            epoch = __shfl_sync(~0u, goal, 0) >> 7;
            int nx = 0;
            __syncwarp();
            while (todo) {
                uint32_t hit;
                asm volatile("{ .reg .pred p, q, t; .reg .u32 c, o, v;\n LAB_EV:\n ld.volatile.shared.v2.u32 {c, o}, [%4]; ld.volatile.shared.u32 v, [%2];\n"
                             " mbarrier.test_wait.parity.shared::cta.b64 t, [%6], 0; add.u32 %1, %1, 1;\n"
                             " sub.u32 v, v, %7; setp.ge.s32 p|q, v, 0; setp.gt.and.u32 q, o, %8, q; @q cp.async.cg.shared.global [%2], [%3], 16; setp.eq.and.u32 p, c, %5, p; setp.ge.or.u32 p, %1, 400000, p;\n"
                             " vote.sync.ballot.b32 %0, p, 0xffffffff; setp.ne.or.u32 p, %0, 0, t;\n @!p bra.uni LAB_EV;\n }"
                             : "=r"(hit), "+r"(it) : "r"(slot), "l"(cp), "r"(pre), "r"(need), "r"(BAR(nx < 5 && !(todo & P.s.xd) ? B_FD + nx : B_X1)), "r"(goal), "r"(need >> 4) : "memory");
                if (hit) {
                    STAMPL(!(lane & 1) && (hit & pbit) && lane < 30, 216 + (lane >> 1));
                    if (hit & pbit) { need = ~0u; if (lbit) bulk_g2s(dst, src, bytes, full); }
                    todo &= ~(hit | (hit >> 1));
                    __syncwarp();
                } else {
                    if (elect()) {
                        tma4d_st(&M.o1, sb + QS + nx * 4096, nx * 128 + cg * 32, 248 - 8 * tb);
                        if (nx == 4) { asm volatile("cp.async.bulk.commit_group;\n cp.async.bulk.wait_group.read 0;" ::: "memory"); pre_add(sb + PRE + 112, true); }
                    }
                    __syncwarp();
                    nx++;
                }
            }
            asm volatile("cp.async.wait_all;" ::: "memory");
            __syncwarp();
            mbar_arrive_if(BAR(B_UD), lane == 0);
        } else {
            mbar_wait(BAR(B_CR), 0);
            epoch = __shfl_sync(~0u, lds32(sb + HT), 0) >> 7;
            asm volatile("barrier.cluster.wait.aligned;" ::: "memory");
            if (warp == 11 && elect()) { mbar_arrive(BAR(B_IN)); pf_map(&M.w[0]); pf_map(&M.w[1]); pf_map(&M.o1); pf_map(&M.w[2]); pf_map(&M.w[3]); pf_map(&M.wd); pf_map(&M.wn); pf_map(&M.out); pf_map(&M.ou2); }
            const int wf = warp - 10, c = lane >> 2, run = 4 * wf + (lane & 3);
            auto mod_fetch = [&](int n, int lane) { asm volatile("cp.async.cg.shared.global [%0], [%1], 16;" :: "r"(sb + RAW + lane * 16), "l"(SC(mod, (((lane >> 3) + (lane >= 24)) * 640 + 128 * n + 32 * cg + (lane & 7) * 4) * 4)) : "memory"); };
            auto mod_put = [&](int n, int lane) {
                uint32_t mv[4];
                _Pragma("unroll 1") for (int it = 0; it < 20000; it++) {
                    asm volatile("cp.async.wait_all;" ::: "memory");
                    __syncwarp();
                    #pragma unroll
                    for (int i = 0; i < 4; i++) mv[i] = lds32(sb + RAW + i * 128 + lane * 4);
                    if (!__any_sync(~0u, (((mv[0] ^ epoch) | (mv[1] ^ epoch) | (mv[2] ^ epoch) | (mv[3] ^ epoch)) & 7) != 0)) break;
                    if (it) asm volatile("nanosleep.u32 150;");
                    mod_fetch(n, lane);
                }
                const float ga = bfround(__uint_as_float(mv[2])), a0 = ga * bfround(__uint_as_float(mv[0])), a1 = ga * bfround(bfround(__uint_as_float(mv[1])) + 1.f), c1 = bfround(__uint_as_float(mv[3])) + 1.f;
                if (n) bar_sync(4, 64);
                asm volatile("st.shared.v2.b32 [%0], {%1, %2};" :: "r"(sb + CT + (lane & 7) * 32 + (lane >> 3) * 8), "r"(pack2(a0, a1)), "r"(pack2(c1, c1)) : "memory");
                __syncwarp();
                mbar_arrive_if(BAR(B_YF + n), lane == 0);
                STAMP(150 + n);
            };
            const int qrow = 63 - 16 * (lane >> 3) - 8 * wf - (lane & 7);
            uint32_t qa = sb + QS + qrow * 64 + (((qrow >> 1) & 3) << 4);
            float s1 = 0.f, s2 = 0.f;
            auto row_stats = [&](uint32_t a) {
                float st[4] = {s1, s2, 0.f, 0.f};
                uint4 v[4];
                #pragma unroll
                for (int i = 0; i < 4; i++) v[i] = lds128(a ^ (i << 4));
                #pragma unroll
                for (int i = 0; i < 16; i++) {
                    const uint32_t u = (&v[i >> 2].x)[i & 3]; const float a0 = bflo(u), a1 = bfhi(u);
                    vadd(st[0], a0); vfma(st[1], a0, a0); vadd(st[2], a1); vfma(st[3], a1, a1);
                    if ((i & 3) == 3) yield();
                }
                s1 = st[0] + st[2]; s2 = st[1] + st[3];
            };
            auto put_stats = [&](uint32_t off) { ll_write1(padd(P.scr, off + (tb * 4 + cg) * 512 + (((qa - sb) >> 3) & 504)), __uint_as_float(tagged(s1, epoch)), __float_as_uint(s2)); };
            _Pragma("unroll 1") for (int r = 0; r < 5; r++) {
                if (r == 4 && wf) mod_fetch(0, lane);
                mbar_wait(BAR(B_Q + r), 0);
                STAMPIF(wf == 0 && r == 4, 62);
                row_stats(qa + r * 4096);
            }
            put_stats(offsetof(Scratch, st1));
            uint32_t tp;
            asm volatile("mov.u32 %0, %%clock;" : "=r"(tp));
            STAMPIF(wf == 0, 40);
            if (wf) mod_put(0, lane);
            s1 = s2 = 0.f;
            wait_clock(tp, P.s.spin);
            {
                const char* sp = SC(st1, (tb * 256 + 63 - 16 * (c >> 1) - (c & 1) - 2 * run) * 8);
                float s, ss;
                _Pragma("unroll 1") for (int it = 0; it < 20000; it++) {
                    uint2 v[4];
                    #pragma unroll
                    for (int i = 0; i < 4; i++) asm volatile("{ .reg .b64 x; ld.relaxed.gpu.global.b64 x, [%2]; mov.b64 {%0, %1}, x; }" : "=r"(v[i].x), "=r"(v[i].y) : "l"(sp + i * 512) : "memory");
                    s = (__uint_as_float(v[0].x) + __uint_as_float(v[1].x)) + (__uint_as_float(v[2].x) + __uint_as_float(v[3].x));
                    ss = (__uint_as_float(v[0].y) + __uint_as_float(v[1].y)) + (__uint_as_float(v[2].y) + __uint_as_float(v[3].y));
                    if (!__any_sync(~0u, (((v[0].x ^ epoch) | (v[1].x ^ epoch) | (v[2].x ^ epoch) | (v[3].x ^ epoch)) & 7) != 0)) break;
                    asm volatile("nanosleep.u32 100;");
                }
                const float mu = s * (1.f / D_), rs = bfround(rsqrtf(fmaxf(ss * (1.f / D_) - mu * mu, 0.f) + 1e-5f));
                const uint32_t mr = pack2(-mu * rs, rs);
                asm volatile("st.shared.u16 [%0], %1; st.shared.u16 [%0+128], %2;" :: "r"(sb + MR + run * 16 + c * 2), "h"((uint16_t)mr), "h"((uint16_t)(mr >> 16)) : "memory");
                STAMPIF(wf == 0, 41);
            }
            const int lw = __shfl_sync(~0u, lane, lane);
            char* zp = SC(z, ((tb >> 1) * 10 + (cg >> 1)) * 16384 + (tb & 1) * 8192 + (cg & 1) * 4096 + wf * 2048 + c * 64 + (((lane ^ (c >> 1)) & 3) << 4));
            _Pragma("unroll 1") for (int r = 0; r < 5; r++) {
                const int lane = lw | P.zero[r];
                const int c = lane >> 2, run = 4 * wf + (lane & 3);
                const int r3 = r - 3 * (r >= 3);
                const uint32_t yo = c * 128 + ((run ^ ((c & 1) << 2)) << 4), ya = sb + YS + r3 * 4096 + yo, ca = sb + CT + c * 32;
                __syncwarp();
                uint32_t x[16];
                auto ldx = [&](int h) { asm volatile("ldmatrix.sync.aligned.m8n8.x4.trans.shared.b16 {%0,%1,%2,%3}, [%4];" : "=r"(x[4 * h]), "=r"(x[4 * h + 1]), "=r"(x[4 * h + 2]), "=r"(x[4 * h + 3]) : "r"(qa ^ (h << 4)) : "memory"); };
                auto stx = [&](int h) { asm volatile("stmatrix.sync.aligned.m8n8.x4.trans.shared.b16 [%0], {%1,%2,%3,%4};" :: "r"(qa ^ (h << 4)), "r"(x[4 * h]), "r"(x[4 * h + 1]), "r"(x[4 * h + 2]), "r"(x[4 * h + 3]) : "memory"); };
                ldx(0); ldx(1);
                const uint4 mu = lds128(sb + MR + run * 16), rs = lds128(sb + MR + 128 + run * 16);
                void* hp = CNT(C_Z + 64 * r + (tb >> 1) + 32 * (lane & 1));
                EARLY(hint_cnt<8>(hp, lane < 2));
                mbar_wait(BAR(B_YF + r), 0);
                STAMPIF(wf == 0, 155 + r);
                const bool mine = (r & 1) == wf && r < 4;
                uint4 y[2], cs;
                _Pragma("unroll 1") for (int tries = 0;; tries++) {
                    y[0] = lds128(ya); y[1] = lds128(ya + 1024); cs = lds128(ca);
                    uint32_t bad;
                    asm("{ .reg .b32 a, b; lop3.b32 a, %1, %2, %5, 0x7e; lop3.b32 b, %3, %4, %5, 0x7e; lop3.b32 %0, a, b, 1, 0xa8; }" : "=r"(bad) : "r"(y[0].x), "r"(y[1].x), "r"(lds32(ya + 2048)), "r"(lds32(ya + 3072)), "r"(epoch));
                    if (!__any_sync(~0u, bad) || tries) break;
                    repair_tile<4, 1024, 2048>(ya, SC(yB, ((r * 4 + cg) * 32 + tb) * 4096) - (sb + YS + r3 * 4096), epoch);
                    STAMP(125);
                }
                #pragma unroll
                for (int h = 0; h < 4; h++) {
                    uint32_t* xh = x + 4 * h; uint4& yh = y[h & 1];
                    #pragma unroll
                    for (int j = 0; j < 4; j++)
                        asm("{ .reg .b16 l, h; .reg .b32 a0, a1, n; mov.b32 {l, h}, %4; mov.b32 a0, {l, l}; mov.b32 a1, {h, h}; fma.rn.bf16x2 n, %0, %2, %3; fma.rn.bf16x2 n, n, a1, a0; fma.rn.bf16x2 %0, n, %1, %0; mul.rn.bf16x2 %1, %0, %5; }"
                            : "+r"(xh[j]), "+r"((&yh.x)[j]) : "r"((&rs.x)[j]), "r"((&mu.x)[j]), "r"((h & 1) ? cs.z : cs.x), "r"((h & 1) ? cs.w : cs.y));
                    (&yh.x)[h] = tagbit((&yh.x)[h], epoch);
                    stg_v4(zp + h * 512, yh.x, yh.y, yh.z, yh.w);
                    if (h < 2) { stx(h); yh = lds128(ya + 2048 + h * 1024); ldx(h + 2); }
                    if (h == 1) { cs = lds128(ca + 16); if (mine) mod_fetch(r + 1, lane); }
                }
                __syncwarp();
                LATE(hint_cnt<8>(hp, lane < 2));
                pre_add(sb + PRE + 84 + r * 8 - 20 * (lane & 1), lane < 1 + (r < 2));
                STAMPIF(wf == 0, 160 + r);
                stx(2); stx(3);
                __syncwarp();
                if (!mine && r < 4) bar_arrive(4, 64);
                if (r == 3 && !wf) {
                    float2 sc[4];
                    ll_read2<2, 2560, 2, 256>(SC(mod, (1920 + (((tile - (tile == 15)) * 11) >> 5) * 128 + 2 * lane) * 4), epoch, sc);
                    #pragma unroll
                    for (int n = 0; n < 4; n++) { const float one = n >> 1;
                        sts32(sb + CS_TAB + ((lane >> 2) + 8 * (n & 1)) * 32 + (lane & 3) * 4 + (n < 2) * 16, pack2(bfround(sc[n].x) + one, bfround(sc[n].y) + one)); }
                    fence_async_smem(); __syncwarp(); mbar_arrive_if(BAR(B_UF), lane == 0);
                    STAMP(52);
                }
                row_stats(qa);
                if (mine) mod_put(r + 1, lane);
                fence_async_smem();
                __syncwarp();
                mbar_arrive_if(BAR(B_FD + r), lane == 0);
                qa += 4096; zp += 32768;
            }
            put_stats(offsetof(Scratch, st2));
            __syncwarp();
            STAMPIF(wf, 53);
        }
        {
            mbar_wait(BAR(B_UD), 0);
            const int n = warp - 9 + (warp == 8);
            _Pragma("unroll 1") for (int h = 0; h < 2; h++) {
                const char* up = SC(ut, (h * 1536 + js * 192 + n * 64 + 2 * lane) * 8);
                uint4 v[5];
                _Pragma("unroll 1") for (int it = 0; it < 20000; it++) {
                    uint32_t bad = 0;
                    #pragma unroll
                    for (int i = 0; i < 5; i++) v[i] = ldg_rlx128(up + i * 24576);
                    #pragma unroll
                    for (int i = 0; i < 5; i++) bad |= (v[i].x ^ epoch) | (v[i].z ^ epoch);
                    if (!__any_sync(~0u, (bad & 7) != 0)) break;
                    asm volatile("nanosleep.u32 100;");
                }
                float f[4];
                #pragma unroll
                for (int j = 0; j < 4; j++) f[j] = (__uint_as_float((&v[0].x)[j]) + __uint_as_float((&v[1].x)[j])) + (__uint_as_float((&v[2].x)[j]) + __uint_as_float((&v[3].x)[j])) + __uint_as_float((&v[4].x)[j]);
                const uint32_t ta = sb + TAB1 + ((n == 2 ? 32 + h * 8 : n * 8 + h * 16) + (lane >> 2)) * 48 + (lane & 3) * 4, th2 = pack2(f[1], f[3]);
                sts32(ta, pack2(f[0], f[2])); sts32(ta + 16, th2); sts32(ta + 32, pack2(f[1] - bflo(th2), f[3] - bfhi(th2)));
            }
            if (lane < 20) sts32(sb + TAB1 + 48 * 48 + lane * 4, 0);
            fence_async_smem();
            __syncwarp();
            if (lane == 0) mbar_arrive(BAR(B_T1));
            STAMPIF(warp == 10, 61);
        }
        if (warp == 11) {
            char* hc = paddv(P.scr, (C_HH + tile * 2 + kh + 32 * (lane & 1)) * 128);
            #pragma unroll
            for (int c = 0; c < 3; c++) { EARLY(hint_cnt<32>(hc + 4 * c, lane < 2)); mbar_wait(BAR(B_HD + (c & 1)), c >> 1); LATE(hint_cnt<32>(hc + 4 * c, lane < 2)); STAMP(176 + c); }
            float2 gbv[3];
            ll_read2<1, 0, 3, 192>(SC(mod, (5 * 640 + dq * 160 + 2 * lane) * 4), epoch, gbv);
            #pragma unroll
            for (int n = 0; n < 3; n++) sts32(sb + GBT + (lane & 3) * 80 + ((lane >> 2) + 6 * n) * 4, pack2(gbv[n].x, gbv[n].y));
            poll_cnt((uint32_t*)paddv(P.scr, C_ZO * 128 + (lds32(sb + HT) & 127)), epoch << 7);
            fence_async_glob();
            __syncwarp();
            mbar_arrive_if(BAR(B_X1), lane == 0);
        } else if (warp == 8) {
            if (elect()) {
                asm volatile("cp.async.bulk.wait_group 0;" ::: "memory");
                fence_async_glob();
                signal_cnt((uint32_t*)paddv(P.scr, C_ZO * 128 + (lds32(sb + HT) & 127)), 1);
            }
            __syncwarp();
            uint32_t rtp = 0;
            mbar_wait(BAR(B_WX), 0);
            _Pragma("unroll 1") for (int v = 0; v < 9; v++) {
                const int c = (v * 11) >> 5, m = v - 3 * c;
                const uint32_t ok = BAR(B_G2F + m + (c == 0 ? 2 : c == 1 ? 0 : 3)), dst = sb + G2A + ((c & 1) ? (m ? m - 1 : 4) : m ? m + 1 : 5) * 16384, a = dst + (lane >> 3) * 516 + (lane & 7) * 16;
                if (c) mbar_wait(ok, 0);
                mbar_wait(BAR(B_AF + v), 1);
                _Pragma("unroll 1") for (int it = 0; it < 1000; it++) {
                    uint32_t w[32], bad = 0;
                    #pragma unroll
                    for (int i = 0; i < 32; i++) w[i] = lds32(a + (i >> 2) * 2048 + (i & 3) * 128);
                    #pragma unroll
                    for (int i = 0; i < 32; i += 4)
                        asm("{ .reg .b32 a, b; lop3.b32 a, %1, %2, %5, 0x7e; lop3.b32 b, %3, %4, %5, 0x7e; lop3.b32 %0, %0, a, b, 0xfe; }" : "+r"(bad) : "r"(w[i]), "r"(w[i + 1]), "r"(w[i + 2]), "r"(w[i + 3]), "r"(epoch));
                    if (!__any_sync(~0u, bad & 1)) break;
                    if (elect()) { mbar_expect(BAR(B_RT), 16384); bulk_g2s(dst, SC(hh, (tile * 24 + (kh * 4 + m + (m >= dq)) * 3 + (c ^ (c < 2))) * 16384), 16384, BAR(B_RT)); }
                    mbar_wait(BAR(B_RT), rtp);
                    rtp ^= 1;
                    STAMP(122);
                }
                mbar_arrive_if(ok, lane == 0);
            }
        } else if (elect()) {
            {
                int g = 0, c = 0, m = 0;
                _Pragma("unroll 1") for (int n = 0; n < 12; n++) {
                    const uint32_t st = sb + g2b_at(g) + rank * 10240, f = BAR(B_G2F + g);
                    mbar_wait_cluster(BAR(B_G2E + g), n >= 6);
                    mbar_expect(f, 20480);
                    if (n < 2 || n == 5) { mbar_arrive(f); tma3d_mc(st, &M.wn, (js * 3 + (n < 2 ? n : 2)) * 64 + rank * 32, dq * 5, f); }
                    else {
                        tma5d_mc(st, &M.wd, ((kh * 4 + m + (m >= dq)) * 3 + (c ^ (c < 2))) * 8 + rank * 4, dq * 5, f);
                        if (++m == 3) { m = 0; c++; }
                    }
                    g = g == 5 ? 0 : g + 1;
                }
            }
        }
        PROF_EXIT();
    }
}

typedef CUresult (*EncodeFn)(CUtensorMap*, CUtensorMapDataType, cuuint32_t, void*, const cuuint64_t*, const cuuint64_t*, const cuuint32_t*, const cuuint32_t*,
                             CUtensorMapInterleave, CUtensorMapSwizzle, CUtensorMapL2promotion, CUtensorMapFloatOOBfill);
void enc(EncodeFn fn, CUtensorMap* m, const void* ptr, int rank, const cuuint64_t* dims, const cuuint64_t* strides, const cuuint32_t* box, CUtensorMapSwizzle sw,
         CUtensorMapL2promotion pr = CU_TENSOR_MAP_L2_PROMOTION_L2_128B) {
    cuuint32_t es[5] = {1, 1, 1, 1, 1};
    fn(m, CU_TENSOR_MAP_DATA_TYPE_BFLOAT16, rank, (void*)ptr, dims, strides, box, es, CU_TENSOR_MAP_INTERLEAVE_NONE, sw, pr, CU_TENSOR_MAP_FLOAT_OOB_FILL_NONE);
}
#define LD(kind, r, t) (((t) << 8) | ((kind) << 4) | (r))
Sched h_sched = {{LD(0,1,1920), LD(1,0,2880), LD(1,1,3274), LD(0,2,3901), LD(1,2,4674), LD(2,0,5056), LD(2,1,5105), LD(2,2,5215), LD(1,3,5562), LD(2,3,5613), LD(0,3,6029), LD(2,4,7135), LD(0,4,7650), LD(1,4,8395), LD(3,0,8901), LD(4,0,9700), LD(4,1,10850), LD(8,0,11550), LD(8,1,11600), LD(4,2,11650), LD(8,2,12000), LD(8,3,12200), LD(4,3,12450)},
                 {0x61, 0x362, 0x4, 0x5, 0x0}, 0, 800, 75, 1048576};
#define PROMO CU_TENSOR_MAP_L2_PROMOTION_L2_128B
}

extern "C" void kernel_launch(void* const* d_in, const int* in_sizes, int n_in, void* d_out, int out_size) {
    void* fnp = nullptr; cudaDriverEntryPointQueryResult st;
    cudaGetDriverEntryPoint("cuTensorMapEncodeTiled", &fnp, cudaEnableDefault, &st);
    EncodeFn fn = (EncodeFn)fnp;
    void* scr;
    cudaGetSymbolAddress(&scr, g_s);
    Maps M; Ptrs P;
    P.k = (const char*)d_in[1]; P.v = (const char*)d_in[2]; P.shift = (const char*)d_in[3];
    P.ssm = (const char*)d_in[4]; P.ssmD = (const char*)d_in[5]; P.Wg = (const char*)d_in[7]; P.Wu = (const char*)d_in[8];
    P.Wd = (const char*)d_in[9]; P.c = (const char*)d_in[10]; P.scr = (char*)scr; P.s = h_sched;
    for (int i = 0; i < 8; i++) P.zero[i] = 0;
    { cuuint64_t d[3] = {640, 256, 8}, s[2] = {8 * 1280, 1280}; cuuint32_t b1[3] = {32, 9, 8}, b2[3] = {32, 8, 8};
      enc(fn, &M.k, P.k, 3, d, s, b1, CU_TENSOR_MAP_SWIZZLE_64B, PROMO); enc(fn, &M.v, P.v, 3, d, s, b2, CU_TENSOR_MAP_SWIZZLE_64B, PROMO); }
    { cuuint64_t d[4] = {640, 2, 256, 4}, s[3] = {1280, 8 * 1280, 2 * 1280}; cuuint32_t b1[4] = {32, 2, 8, 4};
      enc(fn, &M.q, d_in[0], 4, d, s, b1, CU_TENSOR_MAP_SWIZZLE_64B, PROMO); enc(fn, &M.o1, d_out, 4, d, s, b1, CU_TENSOR_MAP_SWIZZLE_64B, PROMO); }
    { cuuint64_t d[3] = {64, 640, 24}, s[2] = {3072, 128}; cuuint32_t bx[2][3] = {{64, 32, 2}, {64, 64, 1}};
      for (int i = 0; i < 4; i++) enc(fn, &M.w[i], (i & 1) ? P.Wu : P.Wg, 3, d, s, bx[i >> 1], CU_TENSOR_MAP_SWIZZLE_128B); }
    { cuuint64_t d[5] = {32, 2, 192, 4, 20}, s[4] = {1280, 8 * 1280, 2 * 1280, 64}; cuuint32_t b1[5] = {32, 2, 4, 4, 5};
      enc(fn, &M.wd, P.Wd, 5, d, s, b1, CU_TENSOR_MAP_SWIZZLE_64B); }
    { cuuint64_t d[3] = {32, 1536, 20}, s[2] = {1280, 64}; cuuint32_t b1[3] = {32, 32, 5};
      enc(fn, &M.wn, P.Wd, 3, d, s, b1, CU_TENSOR_MAP_SWIZZLE_64B); }
    { cuuint64_t d[2] = {3840, 640}, s[1] = {7680}; cuuint32_t b1[2] = {64, 160};
      enc(fn, &M.wm, d_in[11], 2, d, s, b1, CU_TENSOR_MAP_SWIZZLE_128B); }
    { cuuint64_t d[2] = {640, 2048}, s[1] = {1280}; cuuint32_t b1[2] = {64, 16}, b2[2] = {32, 16};
      enc(fn, &M.out, d_out, 2, d, s, b1, CU_TENSOR_MAP_SWIZZLE_128B); enc(fn, &M.ou2, d_out, 2, d, s, b2, CU_TENSOR_MAP_SWIZZLE_64B); }
    cudaFuncSetAttribute(fused_kernel, cudaFuncAttributeMaxDynamicSharedMemorySize, SMEM_BYTES);
    fused_kernel<<<132, 384, SMEM_BYTES>>>(P, M);
}
```

```cpp
#include <cuda_runtime.h>
#include <cuda_bf16.h>
#include <cuda.h>
#include <stdint.h>
#include <stddef.h>
#include <type_traits>

namespace {

constexpr int S_ = 2048, D_ = 640;

struct Scratch {
    uint32_t cnt[8 * 2048];
    uint4 kvT[D_ * 256];
    uint4 yB[D_ * 256];
    uint4 z[D_ * 256];
    uint4 hh[16 * 24 * 1024];
    uint2 st1[128 * 64], st2[128 * 64];
    uint32_t mod[3840];
    uint2 ut[5 * 3072];
};
__device__ __align__(8192) Scratch g_s;
#define SC(f, off) padd(P.scr, (uint32_t)offsetof(Scratch, f) + (off))
constexpr int C_KV = 0  , C_ZO = 31, C_Y = 64, C_Z = 128  , C_HH = 448  ;
#define GSTAMPIF(c, i) do {} while (0)
#define STAMPIF(c, i) do {} while (0)
#define STAMPL(c, i) do {} while (0)
#define PROF_EXIT() do {} while (0)
#define KSTAMP(c, i) do {} while (0)
#define STAMP(i) do {} while (0)

constexpr uint32_t WR = 163840, MISC = 229376, SMEM_BYTES = 232448;
constexpr uint32_t XP = 4112, KVP = 8704, PP = 4352;
constexpr uint32_t PB = 65536, XB = PB + 4 * PP;
constexpr uint32_t UST = 98304;
constexpr uint32_t KV3 = WR + 32768, SHT = KV3 + 2 * KVP;
constexpr uint32_t DS = SHT + 5120, H4 = DS + 1280, HO0 = H4 + XP + 48, HO1 = 4 * XP + 32;
__host__ __device__ constexpr uint32_t h_at(int r) { return r == 4 ? H4 : r * XP; }
static_assert(HO0 % 128 == 64 && H4 % 128 == 0 && HO1 % 128 == 96 && HO0 + XP <= MISC, "bank offsets");
constexpr uint32_t QS = 131072, YS = QS + 20480;
__host__ __device__ constexpr uint32_t kv_at(int r) { return r * KVP + (r >= 3 ? KV3 - 3 * KVP : UST); }
__host__ __device__ constexpr uint32_t x_at(int r) { return XB - (r & 1) * 32768 + (r >> 1) * XP; }
constexpr uint32_t BARS = MISC, HT = MISC + 680, TAB1 = MISC + 688, TAB2 = TAB1 + 32 * 48;
constexpr uint32_t CT = TAB1, RAW = TAB1 + 256, MR = TAB1 + 768, CS_TAB = TAB1 + 1024, PS = TAB1 + 1632, PRE = PS + 512;
constexpr uint32_t GBT = TAB1 + 64, G2B = 8192, G2A = 131072;
__host__ __device__ constexpr uint32_t g2b_at(int g) { return G2B + (g < 4 ? g + 2 : g - 4) * 20480; }
__host__ __device__ constexpr uint32_t w2_at(int it) { return it < 4 ? WR + it * 16384 : (it & 1) ? (it >> 1) * 16384 - 32768 : WR + (it >> 1) * 16384 - 32768; }
__host__ __device__ constexpr int w2_bar(int it);
enum { B_KV = 0, B_H = 5, B_Q = 10, B_XF = 15, B_YF = 20, B_AF = 25, B_WF = 35, B_G2F = 39, B_CR = 45, B_RT = 46, B_WE = 47, B_G2E = 51,
       B_S0 = 57, B_HD = 58, B_UD = 60, B_T1 = 61, B_FF = 62  , B_GO = 65, B_UF = 66, B_X1 = 67, B_FD = 68, B_WX = 73  , B_HE = 76  , NBARS = 79 };
__host__ __device__ constexpr uint32_t bar_count(int i) {
    return (i > B_XF && i < B_YF) ? 5 : ((i >= B_YF && i < B_AF) || (i >= B_G2F && i < B_CR)) ? 2 : i < B_WE ? 1 : i < B_S0 ? 16 : i < B_UD ? 8 : i == B_UD ? 9 : i == B_T1 ? 3 : i == B_X1 ? 1 : i == B_FF ? 6 : i == B_FF + 1 ? 4 : (i == B_GO || i == B_FF + 2) ? 8 : i < B_WX ? 2 : i < B_HE ? 1 : 8;
}
__host__ __device__ constexpr int w2_bar(int it) { return it < 4 ? B_WF + it : ((it & 1) ? B_WX : B_WF) + (it >> 1) - 2; }
#define SG 5
#define RD4 0
#define PF2 0
#define CSM 0x01040000u
#define MORD 1
#define ESPLIT 1
#define PW 0
#define EARLY(x)
#define LATE(x) x
#define HPS 0xca864310u
#define B2S 0xa88765
#define KB_UT 4
#define NPF 64
#define FA 24
#define MAP 2
#define FMAP 0
constexpr int NLD = 28;
struct Sched { uint32_t ld[NLD], wl[5], d_sp, spin, g_sp, xd; };

#define LD(kind, r, t) (((t) << 8) | ((kind) << 4) | (r))
constexpr Sched c_sched = {{LD(0,1,1340), LD(1,0,2360), LD(1,1,2520), LD(0,2,3668), LD(1,2,4232), LD(2,0,4598), LD(2,1,4926), LD(2,2,5130), LD(0,3,5475), LD(2,3,6064), LD(1,3,6383), LD(2,4,6383), LD(0,4,7368), LD(1,4,8156), LD(3,0,8614), LD(4,0,9110), LD(8,0,9110), LD(4,1,10150), LD(8,1,10550), LD(8,2,10570), LD(4,2,10570), LD(8,3,11800), LD(4,3,12390)},
                 {0x61, 0x632, 0x4, 0x5, 0x0}, 1500, 800, 300, 16384};
#define SCH(f) (std::integral_constant<uint32_t, c_sched.f>::value)

__device__ __forceinline__ uint32_t smem_u32(const void* p) { return (uint32_t)__cvta_generic_to_shared(p); }
__device__ __forceinline__ void mbar_init(uint32_t bar, uint32_t cnt) { asm volatile("mbarrier.init.shared::cta.b64 [%0], %1;" :: "r"(bar), "r"(cnt) : "memory"); }
__device__ __forceinline__ void mbar_expect(uint32_t bar, uint32_t bytes) { asm volatile("mbarrier.arrive.expect_tx.shared::cta.b64 _, [%0], %1;" :: "r"(bar), "r"(bytes) : "memory"); }
__device__ __forceinline__ void mbar_arrive(uint32_t bar) { asm volatile("mbarrier.arrive.shared::cta.b64 _, [%0];" :: "r"(bar) : "memory"); }
__device__ __forceinline__ void mbar_arrive_if(uint32_t bar, bool p) { asm volatile("{ .reg .pred p; setp.ne.b32 p, %1, 0; @p mbarrier.arrive.shared::cta.b64 _, [%0]; }" :: "r"(bar), "r"((int)p) : "memory"); }
__device__ __forceinline__ void mbar_arrive_remote_if(uint32_t bar, bool p) { asm volatile("{ .reg .pred p; setp.ne.b32 p, %1, 0; @p mbarrier.arrive.shared::cluster.b64 _, [%0]; }" :: "r"(bar), "r"((int)p) : "memory"); }
__device__ __forceinline__ void mbar_wait(uint32_t bar, uint32_t parity) {
    asm volatile("{\n .reg .pred p, q; .reg .u32 c; mov.u32 c, 0;\n LAB_WAIT:\n mbarrier.try_wait.parity.shared::cta.b64 p, [%0], %1;\n"
                 " add.u32 c, c, 1; setp.lt.and.u32 q, c, 16384, !p;\n @q bra LAB_WAIT;\n }" :: "r"(bar), "r"(parity) : "memory");
}
__device__ __forceinline__ bool mbar_test(uint32_t bar, uint32_t parity) {
    uint32_t ok; asm volatile("{ .reg .pred p; mbarrier.test_wait.parity.shared::cta.b64 p, [%1], %2; selp.u32 %0, 1, 0, p; }" : "=r"(ok) : "r"(bar), "r"(parity) : "memory"); return ok;
}
__device__ __forceinline__ void wait_clock(uint32_t t0, uint32_t d) {
    asm volatile("{\n .reg .pred p; .reg .u32 t;\n LAB_CLK:\n mov.u32 t, %%clock; sub.u32 t, t, %0; setp.lt.u32 p, t, %1;\n @p bra LAB_CLK;\n }" :: "r"(t0), "r"(d) : "memory");
}
__device__ __forceinline__ void pause(uint32_t d) { uint32_t t; asm volatile("mov.u32 %0, %%clock;" : "=r"(t)); wait_clock(t, d); }
__device__ __forceinline__ void mbar_wait_cluster(uint32_t bar, uint32_t parity) {
    asm volatile("{\n .reg .pred p, q; .reg .u32 c; mov.u32 c, 0;\n LAB_WAIT:\n mbarrier.try_wait.parity.acquire.cluster.shared::cta.b64 p, [%0], %1;\n"
                 " add.u32 c, c, 1; setp.lt.and.u32 q, c, 16384, !p;\n @q bra LAB_WAIT;\n }" :: "r"(bar), "r"(parity) : "memory");
}
__device__ __forceinline__ bool elect() { uint32_t p; asm volatile("{ .reg .pred p; elect.sync _|p, 0xffffffff; selp.u32 %0, 1, 0, p; }" : "=r"(p)); return p; }
__device__ __forceinline__ void pf_map(const CUtensorMap* m) { asm volatile("prefetch.tensormap [%0];" :: "l"(m) : "memory"); }
__device__ __forceinline__ void bar_sync(int id, int n) { asm volatile("bar.sync %0, %1;" :: "r"(id), "r"(n) : "memory"); }
__device__ __forceinline__ void bar_arrive(int id, int n) { asm volatile("bar.arrive %0, %1;" :: "r"(id), "r"(n) : "memory"); }
__device__ __forceinline__ void fence_async_smem() { asm volatile("fence.proxy.async.shared::cta;" ::: "memory"); }
__device__ __forceinline__ void fence_async_glob() { asm volatile("fence.proxy.async.global;" ::: "memory"); }
__device__ __forceinline__ void bulk_g2s(uint32_t dst, const void* src, uint32_t bytes, uint32_t bar) {
    asm volatile("cp.async.bulk.shared::cluster.global.mbarrier::complete_tx::bytes [%0], [%1], %2, [%3];" :: "r"(dst), "l"(src), "r"(bytes), "r"(bar) : "memory");
}
__device__ __forceinline__ void pf_l2(const void* src, uint32_t bytes) { asm volatile("cp.async.bulk.prefetch.L2.global [%0], %1;" :: "l"(src), "r"(bytes) : "memory"); }
__device__ __forceinline__ void tma2d(uint32_t dst, const CUtensorMap* m, int c0, int c1, uint32_t bar) {
    asm volatile("cp.async.bulk.tensor.2d.shared::cluster.global.mbarrier::complete_tx::bytes [%0], [%1, {%3, %4}], [%2];" :: "r"(dst), "l"(m), "r"(bar), "r"(c0), "r"(c1) : "memory");
}
__device__ __forceinline__ void tma3d(uint32_t dst, const CUtensorMap* m, int c0, int c1, int c2, uint32_t bar) {
    asm volatile("cp.async.bulk.tensor.3d.shared::cluster.global.mbarrier::complete_tx::bytes [%0], [%1, {%3, %4, %5}], [%2];" :: "r"(dst), "l"(m), "r"(bar), "r"(c0), "r"(c1), "r"(c2) : "memory");
}
__device__ __forceinline__ void tma4d(uint32_t dst, const CUtensorMap* m, int c0, int c2, uint32_t bar) {
    asm volatile("cp.async.bulk.tensor.4d.shared::cluster.global.mbarrier::complete_tx::bytes [%0], [%1, {%3, %5, %4, %5}], [%2];" :: "r"(dst), "l"(m), "r"(bar), "r"(c0), "r"(c2), "r"(0) : "memory");
}
__device__ __forceinline__ void tma4d_st(const CUtensorMap* m, uint32_t src, int c0, int c2) {
    asm volatile("cp.async.bulk.tensor.4d.global.shared::cta.bulk_group [%0, {%2, %4, %3, %4}], [%1];" :: "l"(m), "r"(src), "r"(c0), "r"(c2), "r"(0) : "memory");
}
__device__ __forceinline__ void tma5d_mc(uint32_t dst, const CUtensorMap* m, int c2, int c4, uint32_t bar) {
    asm volatile("cp.async.bulk.tensor.5d.shared::cluster.global.mbarrier::complete_tx::bytes.multicast::cluster [%0], [%1, {%5, %5, %3, %5, %4}], [%2], %6;"
                 :: "r"(dst), "l"(m), "r"(bar), "r"(c2), "r"(c4), "r"(0), "h"((uint16_t)3) : "memory");
}
__device__ __forceinline__ void tma3d_mc(uint32_t dst, const CUtensorMap* m, int c1, int c2, uint32_t bar, uint16_t mask = 3) {
    asm volatile("cp.async.bulk.tensor.3d.shared::cluster.global.mbarrier::complete_tx::bytes.multicast::cluster [%0], [%1, {%5, %3, %4}], [%2], %6;"
                 :: "r"(dst), "l"(m), "r"(bar), "r"(c1), "r"(c2), "r"(0), "h"(mask) : "memory");
}
__device__ __forceinline__ void tma2d_red(const CUtensorMap* m, uint32_t src, int c0, int c1) {
    asm volatile("cp.reduce.async.bulk.tensor.2d.global.shared::cta.add.bulk_group [%0, {%2, %3}], [%1];" :: "l"(m), "r"(src), "r"(c0), "r"(c1) : "memory");
}
#define FENCE_REL "fence.release.gpu;"
__device__ __forceinline__ void signal_cnt(uint32_t* c, uint32_t inc) {
    asm volatile(FENCE_REL "\n fence.proxy.async.global;\n red.relaxed.gpu.global.add.u32 [%0], %1; red.relaxed.gpu.global.add.u32 [%0+4096], %1;" :: "l"(c), "r"(inc) : "memory");
}
template<int INC = 4> __device__ __forceinline__ void hint_cnt(void* c, bool p) { asm volatile("{ .reg .pred p; setp.ne.b32 p, %1, 0; @p red.relaxed.gpu.global.add.u32 [%0], %2; }" :: "l"(c), "r"((int)p), "n"(INC) : "memory"); }
__device__ __forceinline__ void pre_add(uint32_t a, bool p) { asm volatile("{ .reg .pred p; setp.ne.b32 p, %1, 0; @p red.shared.add.u32 [%0], 1; }" :: "r"(a), "r"((int)p) : "memory"); }
__device__ __forceinline__ uint32_t tagbit(uint32_t x, uint32_t tag) { uint32_t r; asm("lop3.b32 %0, %1, %2, 1, 0xd8;" : "=r"(r) : "r"(x), "r"(tag)); return r; }
__device__ __forceinline__ void stg_v4(void* p, uint32_t x, uint32_t y, uint32_t z, uint32_t w) { asm volatile("st.relaxed.gpu.global.v4.b32 [%0], {%1,%2,%3,%4};" :: "l"(p), "r"(x), "r"(y), "r"(z), "r"(w) : "memory"); }
template<int OFF> __device__ __forceinline__ void stg_tag2(char* p, uint32_t x, uint32_t y, uint32_t z, uint32_t w, uint32_t x2, uint32_t y2, uint32_t z2, uint32_t w2, uint32_t tag) {
    stg_v4(p, tagbit(x, tag), y, z, w); stg_v4(p + OFF, tagbit(x2, tag), y2, z2, w2);
}
__device__ __forceinline__ void wait_dual(const uint32_t* c, uint32_t slot, uint32_t d, uint32_t target, uint32_t bar, uint32_t par) {
    asm volatile("{\n .reg .pred p, q, t; .reg .u32 n, v, w; mov.u32 n, 0;\n LAB_PD:\n ld.volatile.shared.u32 v, [%2]; ld.volatile.shared.u32 w, [%2+16];\n"
                 " mbarrier.test_wait.parity.shared::cta.b64 t, [%4], %5;\n"
                 " sub.u32 v, v, %3; sub.u32 w, w, %3; and.b32 v, v, w; setp.ge.and.s32 p, v, 0, t;\n @p bra LAB_PDD;\n"
                 " and.b32 w, n, 1; setp.eq.u32 q, w, 0; @q cp.async.cg.shared.global [%1], [%0], 16; @q cp.async.cg.shared.global [%1+16], [%0+4096], 16;\n"
                 " add.u32 n, n, 1; setp.lt.u32 q, n, 200000;\n @q bra LAB_PD;\n LAB_PDD:\n }" :: "l"(c), "r"(slot), "r"(slot + d), "r"(target), "r"(bar), "r"(par) : "memory");
}
__device__ __forceinline__ void poll_cnt(const uint32_t* c, uint32_t target) {
    asm volatile("{\n .reg .pred p, q; .reg .u32 c, v; mov.u32 c, 0;\n LAB_POLL:\n ld.relaxed.gpu.global.u32 v, [%0];\n sub.u32 v, v, %1; setp.ge.s32 p, v, 0;\n @p bra LAB_PDONE;\n"
                 " add.u32 c, c, 1; setp.lt.u32 q, c, 20000;\n @q bra LAB_POLL;\n LAB_PDONE:\n fence.acquire.gpu;\n }" :: "l"(c), "r"(target) : "memory");
}
template<int N1, int S1, int N2, int S2> __device__ __forceinline__ void ll_read2(const char* p, uint32_t tag, float2* out) {
    constexpr int N = N1 * N2;
    _Pragma("unroll 1") for (int it = 0; it < 20000; it++) {
        uint32_t bad = 0;
        #pragma unroll
        for (int i = 0; i < N; i++) asm volatile("ld.relaxed.gpu.global.v2.f32 {%0, %1}, [%2];" : "=f"(out[i].x), "=f"(out[i].y) : "l"(p + (i / N2) * S1 + (i % N2) * S2) : "memory");
        #pragma unroll
        for (int i = 0; i < N; i++) bad |= (__float_as_uint(out[i].x) ^ tag) | (__float_as_uint(out[i].y) ^ tag);
        if (!__any_sync(~0u, (bad & 7) != 0)) break;
        asm volatile("nanosleep.u32 200;");
    }
}
__device__ __forceinline__ void ll_write1(void* p, float a, uint32_t tag) {
    asm volatile("{ .reg .b64 x; mov.b64 x, {%1, %2}; st.relaxed.gpu.global.b64 [%0], x; }" :: "l"(p), "r"(__float_as_uint(a)), "r"(tag) : "memory");
}
__device__ __forceinline__ uint4 lds128(uint32_t a) { uint4 v; asm volatile("ld.shared.v4.b32 {%0,%1,%2,%3}, [%4];" : "=r"(v.x), "=r"(v.y), "=r"(v.z), "=r"(v.w) : "r"(a) : "memory"); return v; }
__device__ __forceinline__ void sts128(uint32_t a, uint32_t x, uint32_t y, uint32_t z, uint32_t w) { asm volatile("st.shared.v4.b32 [%0], {%1,%2,%3,%4};" :: "r"(a), "r"(x), "r"(y), "r"(z), "r"(w) : "memory"); }
__device__ __forceinline__ void sts32(uint32_t a, uint32_t x) { asm volatile("st.shared.b32 [%0], %1;" :: "r"(a), "r"(x) : "memory"); }
__device__ __forceinline__ uint4 ldg_rlx128(const void* p) { uint4 v; asm volatile("{ .reg .b64 x, y; ld.relaxed.gpu.global.v2.b64 {x, y}, [%4]; mov.b64 {%0, %1}, x; mov.b64 {%2, %3}, y; }" : "=r"(v.x), "=r"(v.y), "=r"(v.z), "=r"(v.w) : "l"(p) : "memory"); return v; }
__device__ __forceinline__ uint32_t lds32(uint32_t a) { uint32_t v; asm volatile("ld.shared.b32 %0, [%1];" : "=r"(v) : "r"(a) : "memory"); return v; }
__device__ __forceinline__ void stg128(void* p, uint32_t x, uint32_t y, uint32_t z, uint32_t w) { asm volatile("st.global.v4.b32 [%0], {%1,%2,%3,%4};" :: "l"(p), "r"(x), "r"(y), "r"(z), "r"(w) : "memory"); }
__device__ __forceinline__ char* padd(const void* p, uint32_t off) { char* r; asm("{ .reg .u64 t; cvt.u64.u32 t, %2; add.u64 %0, %1, t; }" : "=l"(r) : "l"(p), "r"(off)); return r; }
__device__ __forceinline__ char* paddv(const void* p, uint32_t off) { char* r; asm volatile("{ .reg .u64 t; cvt.u64.u32 t, %2; add.u64 %0, %1, t; }" : "=l"(r) : "l"(p), "r"(off)); return r; }
__device__ __forceinline__ uint32_t prmt(uint32_t a, uint32_t b, uint32_t s) { uint32_t r; asm("prmt.b32 %0, %1, %2, %3;" : "=r"(r) : "r"(a), "r"(b), "r"(s)); return r; }
__device__ __forceinline__ uint32_t pack2(float lo, float hi) { uint32_t r; asm("cvt.rn.bf16x2.f32 %0, %1, %2;" : "=r"(r) : "f"(hi), "f"(lo)); return r; }
__device__ __forceinline__ uint32_t pack2relu(float lo, float hi) { uint32_t r; asm("cvt.rn.relu.bf16x2.f32 %0, %1, %2;" : "=r"(r) : "f"(hi), "f"(lo)); return r; }
__device__ __forceinline__ float bflo(uint32_t w) { return __uint_as_float(w << 16); }
__device__ __forceinline__ float bfhi(uint32_t w) { return __uint_as_float(w & 0xffff0000u); }
__device__ __forceinline__ float bfround(float x) { return bflo(pack2(x, x)); }
__device__ __forceinline__ uint32_t hmul2(uint32_t a, uint32_t b) { uint32_t r; asm("mul.rn.bf16x2 %0, %1, %2;" : "=r"(r) : "r"(a), "r"(b)); return r; }
__device__ __forceinline__ uint32_t hadd2(uint32_t a, uint32_t b) { uint32_t r; asm("add.rn.bf16x2 %0, %1, %2;" : "=r"(r) : "r"(a), "r"(b)); return r; }
__device__ __forceinline__ uint32_t hsub2(uint32_t a, uint32_t b) { uint32_t r; asm("sub.rn.bf16x2 %0, %1, %2;" : "=r"(r) : "r"(a), "r"(b)); return r; }
__device__ __forceinline__ uint32_t hfma2(uint32_t a, uint32_t b, uint32_t c) { uint32_t r; asm("fma.rn.bf16x2 %0, %1, %2, %3;" : "=r"(r) : "r"(a), "r"(b), "r"(c)); return r; }
__device__ __forceinline__ void wg_fence() { asm volatile("wgmma.fence.sync.aligned;" ::: "memory"); }
__device__ __forceinline__ void wg_commit() { asm volatile("wgmma.commit_group.sync.aligned;" ::: "memory"); }
template<int N> __device__ __forceinline__ void wg_wait() { asm volatile("wgmma.wait_group.sync.aligned %0;" :: "n"(N) : "memory"); }
template<int N> __device__ __forceinline__ void pin(float* d) {
    #pragma unroll
    for (int i = 0; i < N; i++) asm volatile("" : "+f"(d[i]) :: "memory");
}
__device__ __forceinline__ uint32_t dlo(uint32_t addr, uint32_t lbo) { return ((addr & 0x3FFFF) >> 4) | ((lbo >> 4) << 16); }
__host__ __device__ constexpr uint32_t dhi(uint32_t sbo, uint32_t sw) { return (sbo >> 4) | (sw << 30); }

template<int N> struct WG;
template<> struct WG<8> { template<int TA, int TB> static __device__ __forceinline__ void ss(float* d, uint32_t alo, uint32_t ahi, uint32_t blo, uint32_t bhi, int sd) {
  asm volatile("{ .reg .pred p; .reg .b64 da, db; mov.b64 da, {%4,%5}; mov.b64 db, {%6,%7}; setp.ne.b32 p, %8, 0;\n"
    "wgmma.mma_async.sync.aligned.m64n8k16.f32.bf16.bf16 {%0,%1,%2,%3}, da, db, p, 1, 1, %9, %10; }"
    : "+f"(d[0]),"+f"(d[1]),"+f"(d[2]),"+f"(d[3])
    : "r"(alo), "r"(ahi), "r"(blo), "r"(bhi), "r"(sd), "n"(TA), "n"(TB)); }
};
template<> struct WG<16> { template<int TA, int TB> static __device__ __forceinline__ void ss(float* d, uint32_t alo, uint32_t ahi, uint32_t blo, uint32_t bhi, int sd) {
  asm volatile("{ .reg .pred p; .reg .b64 da, db; mov.b64 da, {%8,%9}; mov.b64 db, {%10,%11}; setp.ne.b32 p, %12, 0;\n"
    "wgmma.mma_async.sync.aligned.m64n16k16.f32.bf16.bf16 {%0,%1,%2,%3,%4,%5,%6,%7}, da, db, p, 1, 1, %13, %14; }"
    : "+f"(d[0]),"+f"(d[1]),"+f"(d[2]),"+f"(d[3]),"+f"(d[4]),"+f"(d[5]),"+f"(d[6]),"+f"(d[7])
    : "r"(alo), "r"(ahi), "r"(blo), "r"(bhi), "r"(sd), "n"(TA), "n"(TB)); }
  template<int TB> static __device__ __forceinline__ void rs(float* d, uint32_t a0, uint32_t a1, uint32_t a2, uint32_t a3, uint32_t blo, uint32_t bhi, int sd) {
  asm volatile("{ .reg .pred p; .reg .b64 db; mov.b64 db, {%12,%13}; setp.ne.b32 p, %15, 0;\n"
    "wgmma.mma_async.sync.aligned.m64n16k16.f32.bf16.bf16 {%0,%1,%2,%3,%4,%5,%6,%7}, {%8,%9,%10,%11}, db, p, 1, 1, %14; }"
    : "+f"(d[0]),"+f"(d[1]),"+f"(d[2]),"+f"(d[3]),"+f"(d[4]),"+f"(d[5]),"+f"(d[6]),"+f"(d[7])
    : "r"(a0), "r"(a1), "r"(a2), "r"(a3), "r"(blo), "r"(bhi), "n"(TB), "r"(sd)); }
};
template<> struct WG<32> { template<int TA, int TB> static __device__ __forceinline__ void ss(float* d, uint32_t alo, uint32_t ahi, uint32_t blo, uint32_t bhi, int sd) {
  asm volatile("{ .reg .pred p; .reg .b64 da, db; mov.b64 da, {%16,%17}; mov.b64 db, {%18,%19}; setp.ne.b32 p, %20, 0;\n"
    "wgmma.mma_async.sync.aligned.m64n32k16.f32.bf16.bf16 {%0,%1,%2,%3,%4,%5,%6,%7,%8,%9,%10,%11,%12,%13,%14,%15}, da, db, p, 1, 1, %21, %22; }"
    : "+f"(d[0]),"+f"(d[1]),"+f"(d[2]),"+f"(d[3]),"+f"(d[4]),"+f"(d[5]),"+f"(d[6]),"+f"(d[7]),"+f"(d[8]),"+f"(d[9]),"+f"(d[10]),"+f"(d[11]),"+f"(d[12]),"+f"(d[13]),"+f"(d[14]),"+f"(d[15])
    : "r"(alo), "r"(ahi), "r"(blo), "r"(bhi), "r"(sd), "n"(TA), "n"(TB)); }
  template<int TB> static __device__ __forceinline__ void rs(float* d, uint32_t a0, uint32_t a1, uint32_t a2, uint32_t a3, uint32_t blo, uint32_t bhi, int sd) {
  asm volatile("{ .reg .pred p; .reg .b64 db; mov.b64 db, {%20,%21}; setp.ne.b32 p, %23, 0;\n"
    "wgmma.mma_async.sync.aligned.m64n32k16.f32.bf16.bf16 {%0,%1,%2,%3,%4,%5,%6,%7,%8,%9,%10,%11,%12,%13,%14,%15}, {%16,%17,%18,%19}, db, p, 1, 1, %22; }"
    : "+f"(d[0]),"+f"(d[1]),"+f"(d[2]),"+f"(d[3]),"+f"(d[4]),"+f"(d[5]),"+f"(d[6]),"+f"(d[7]),"+f"(d[8]),"+f"(d[9]),"+f"(d[10]),"+f"(d[11]),"+f"(d[12]),"+f"(d[13]),"+f"(d[14]),"+f"(d[15])
    : "r"(a0), "r"(a1), "r"(a2), "r"(a3), "r"(blo), "r"(bhi), "n"(TB), "r"(sd)); }
};
template<> struct WG<48> { template<int TA, int TB> static __device__ __forceinline__ void ss(float* d, uint32_t alo, uint32_t ahi, uint32_t blo, uint32_t bhi, int sd) {
  asm volatile("{ .reg .pred p; .reg .b64 da, db; mov.b64 da, {%24,%25}; mov.b64 db, {%26,%27}; setp.ne.b32 p, %28, 0;\n"
    "wgmma.mma_async.sync.aligned.m64n48k16.f32.bf16.bf16 {%0,%1,%2,%3,%4,%5,%6,%7,%8,%9,%10,%11,%12,%13,%14,%15,%16,%17,%18,%19,%20,%21,%22,%23}, da, db, p, 1, 1, %29, %30; }"
    : "+f"(d[0]),"+f"(d[1]),"+f"(d[2]),"+f"(d[3]),"+f"(d[4]),"+f"(d[5]),"+f"(d[6]),"+f"(d[7]),"+f"(d[8]),"+f"(d[9]),"+f"(d[10]),"+f"(d[11]),"+f"(d[12]),"+f"(d[13]),"+f"(d[14]),"+f"(d[15]),"+f"(d[16]),"+f"(d[17]),"+f"(d[18]),"+f"(d[19]),"+f"(d[20]),"+f"(d[21]),"+f"(d[22]),"+f"(d[23])
    : "r"(alo), "r"(ahi), "r"(blo), "r"(bhi), "r"(sd), "n"(TA), "n"(TB)); }
  template<int TB> static __device__ __forceinline__ void rs(float* d, uint32_t a0, uint32_t a1, uint32_t a2, uint32_t a3, uint32_t blo, uint32_t bhi, int sd) {
  asm volatile("{ .reg .pred p; .reg .b64 db; mov.b64 db, {%28,%29}; setp.ne.b32 p, %31, 0;\n"
    "wgmma.mma_async.sync.aligned.m64n48k16.f32.bf16.bf16 {%0,%1,%2,%3,%4,%5,%6,%7,%8,%9,%10,%11,%12,%13,%14,%15,%16,%17,%18,%19,%20,%21,%22,%23}, {%24,%25,%26,%27}, db, p, 1, 1, %30; }"
    : "+f"(d[0]),"+f"(d[1]),"+f"(d[2]),"+f"(d[3]),"+f"(d[4]),"+f"(d[5]),"+f"(d[6]),"+f"(d[7]),"+f"(d[8]),"+f"(d[9]),"+f"(d[10]),"+f"(d[11]),"+f"(d[12]),"+f"(d[13]),"+f"(d[14]),"+f"(d[15]),"+f"(d[16]),"+f"(d[17]),"+f"(d[18]),"+f"(d[19]),"+f"(d[20]),"+f"(d[21]),"+f"(d[22]),"+f"(d[23])
    : "r"(a0), "r"(a1), "r"(a2), "r"(a3), "r"(blo), "r"(bhi), "n"(TB), "r"(sd)); }
};
template<> struct WG<64> { template<int TA, int TB> static __device__ __forceinline__ void ss(float* d, uint32_t alo, uint32_t ahi, uint32_t blo, uint32_t bhi, int sd) {
  asm volatile("{ .reg .pred p; .reg .b64 da, db; mov.b64 da, {%32,%33}; mov.b64 db, {%34,%35}; setp.ne.b32 p, %36, 0;\n"
    "wgmma.mma_async.sync.aligned.m64n64k16.f32.bf16.bf16 {%0,%1,%2,%3,%4,%5,%6,%7,%8,%9,%10,%11,%12,%13,%14,%15,%16,%17,%18,%19,%20,%21,%22,%23,%24,%25,%26,%27,%28,%29,%30,%31}, da, db, p, 1, 1, %37, %38; }"
    : "+f"(d[0]),"+f"(d[1]),"+f"(d[2]),"+f"(d[3]),"+f"(d[4]),"+f"(d[5]),"+f"(d[6]),"+f"(d[7]),"+f"(d[8]),"+f"(d[9]),"+f"(d[10]),"+f"(d[11]),"+f"(d[12]),"+f"(d[13]),"+f"(d[14]),"+f"(d[15]),"+f"(d[16]),"+f"(d[17]),"+f"(d[18]),"+f"(d[19]),"+f"(d[20]),"+f"(d[21]),"+f"(d[22]),"+f"(d[23]),"+f"(d[24]),"+f"(d[25]),"+f"(d[26]),"+f"(d[27]),"+f"(d[28]),"+f"(d[29]),"+f"(d[30]),"+f"(d[31])
    : "r"(alo), "r"(ahi), "r"(blo), "r"(bhi), "r"(sd), "n"(TA), "n"(TB)); }
  template<int TB> static __device__ __forceinline__ void rs(float* d, uint32_t a0, uint32_t a1, uint32_t a2, uint32_t a3, uint32_t blo, uint32_t bhi, int sd) {
  asm volatile("{ .reg .pred p; .reg .b64 db; mov.b64 db, {%36,%37}; setp.ne.b32 p, %39, 0;\n"
    "wgmma.mma_async.sync.aligned.m64n64k16.f32.bf16.bf16 {%0,%1,%2,%3,%4,%5,%6,%7,%8,%9,%10,%11,%12,%13,%14,%15,%16,%17,%18,%19,%20,%21,%22,%23,%24,%25,%26,%27,%28,%29,%30,%31}, {%32,%33,%34,%35}, db, p, 1, 1, %38; }"
    : "+f"(d[0]),"+f"(d[1]),"+f"(d[2]),"+f"(d[3]),"+f"(d[4]),"+f"(d[5]),"+f"(d[6]),"+f"(d[7]),"+f"(d[8]),"+f"(d[9]),"+f"(d[10]),"+f"(d[11]),"+f"(d[12]),"+f"(d[13]),"+f"(d[14]),"+f"(d[15]),"+f"(d[16]),"+f"(d[17]),"+f"(d[18]),"+f"(d[19]),"+f"(d[20]),"+f"(d[21]),"+f"(d[22]),"+f"(d[23]),"+f"(d[24]),"+f"(d[25]),"+f"(d[26]),"+f"(d[27]),"+f"(d[28]),"+f"(d[29]),"+f"(d[30]),"+f"(d[31])
    : "r"(a0), "r"(a1), "r"(a2), "r"(a3), "r"(blo), "r"(bhi), "n"(TB), "r"(sd)); }
};
template<> struct WG<80> { template<int TA, int TB> static __device__ __forceinline__ void ss(float* d, uint32_t alo, uint32_t ahi, uint32_t blo, uint32_t bhi, int sd) {
  asm volatile("{ .reg .pred p; .reg .b64 da, db; mov.b64 da, {%40,%41}; mov.b64 db, {%42,%43}; setp.ne.b32 p, %44, 0;\n"
    "wgmma.mma_async.sync.aligned.m64n80k16.f32.bf16.bf16 {%0,%1,%2,%3,%4,%5,%6,%7,%8,%9,%10,%11,%12,%13,%14,%15,%16,%17,%18,%19,%20,%21,%22,%23,%24,%25,%26,%27,%28,%29,%30,%31,%32,%33,%34,%35,%36,%37,%38,%39}, da, db, p, 1, 1, %45, %46; }"
    : "+f"(d[0]),"+f"(d[1]),"+f"(d[2]),"+f"(d[3]),"+f"(d[4]),"+f"(d[5]),"+f"(d[6]),"+f"(d[7]),"+f"(d[8]),"+f"(d[9]),"+f"(d[10]),"+f"(d[11]),"+f"(d[12]),"+f"(d[13]),"+f"(d[14]),"+f"(d[15]),"+f"(d[16]),"+f"(d[17]),"+f"(d[18]),"+f"(d[19]),"+f"(d[20]),"+f"(d[21]),"+f"(d[22]),"+f"(d[23]),"+f"(d[24]),"+f"(d[25]),"+f"(d[26]),"+f"(d[27]),"+f"(d[28]),"+f"(d[29]),"+f"(d[30]),"+f"(d[31]),"+f"(d[32]),"+f"(d[33]),"+f"(d[34]),"+f"(d[35]),"+f"(d[36]),"+f"(d[37]),"+f"(d[38]),"+f"(d[39])
    : "r"(alo), "r"(ahi), "r"(blo), "r"(bhi), "r"(sd), "n"(TA), "n"(TB)); }
  template<int TB> static __device__ __forceinline__ void rs(float* d, uint32_t a0, uint32_t a1, uint32_t a2, uint32_t a3, uint32_t blo, uint32_t bhi, int sd) {
  asm volatile("{ .reg .pred p; .reg .b64 db; mov.b64 db, {%44,%45}; setp.ne.b32 p, %47, 0;\n"
    "wgmma.mma_async.sync.aligned.m64n80k16.f32.bf16.bf16 {%0,%1,%2,%3,%4,%5,%6,%7,%8,%9,%10,%11,%12,%13,%14,%15,%16,%17,%18,%19,%20,%21,%22,%23,%24,%25,%26,%27,%28,%29,%30,%31,%32,%33,%34,%35,%36,%37,%38,%39}, {%40,%41,%42,%43}, db, p, 1, 1, %46; }"
    : "+f"(d[0]),"+f"(d[1]),"+f"(d[2]),"+f"(d[3]),"+f"(d[4]),"+f"(d[5]),"+f"(d[6]),"+f"(d[7]),"+f"(d[8]),"+f"(d[9]),"+f"(d[10]),"+f"(d[11]),"+f"(d[12]),"+f"(d[13]),"+f"(d[14]),"+f"(d[15]),"+f"(d[16]),"+f"(d[17]),"+f"(d[18]),"+f"(d[19]),"+f"(d[20]),"+f"(d[21]),"+f"(d[22]),"+f"(d[23]),"+f"(d[24]),"+f"(d[25]),"+f"(d[26]),"+f"(d[27]),"+f"(d[28]),"+f"(d[29]),"+f"(d[30]),"+f"(d[31]),"+f"(d[32]),"+f"(d[33]),"+f"(d[34]),"+f"(d[35]),"+f"(d[36]),"+f"(d[37]),"+f"(d[38]),"+f"(d[39])
    : "r"(a0), "r"(a1), "r"(a2), "r"(a3), "r"(blo), "r"(bhi), "n"(TB), "r"(sd)); }
};
template<> struct WG<96> { template<int TA, int TB> static __device__ __forceinline__ void ss(float* d, uint32_t alo, uint32_t ahi, uint32_t blo, uint32_t bhi, int sd) {
  asm volatile("{ .reg .pred p; .reg .b64 da, db; mov.b64 da, {%48,%49}; mov.b64 db, {%50,%51}; setp.ne.b32 p, %52, 0;\n"
    "wgmma.mma_async.sync.aligned.m64n96k16.f32.bf16.bf16 {%0,%1,%2,%3,%4,%5,%6,%7,%8,%9,%10,%11,%12,%13,%14,%15,%16,%17,%18,%19,%20,%21,%22,%23,%24,%25,%26,%27,%28,%29,%30,%31,%32,%33,%34,%35,%36,%37,%38,%39,%40,%41,%42,%43,%44,%45,%46,%47}, da, db, p, 1, 1, %53, %54; }"
    : "+f"(d[0]),"+f"(d[1]),"+f"(d[2]),"+f"(d[3]),"+f"(d[4]),"+f"(d[5]),"+f"(d[6]),"+f"(d[7]),"+f"(d[8]),"+f"(d[9]),"+f"(d[10]),"+f"(d[11]),"+f"(d[12]),"+f"(d[13]),"+f"(d[14]),"+f"(d[15]),"+f"(d[16]),"+f"(d[17]),"+f"(d[18]),"+f"(d[19]),"+f"(d[20]),"+f"(d[21]),"+f"(d[22]),"+f"(d[23]),"+f"(d[24]),"+f"(d[25]),"+f"(d[26]),"+f"(d[27]),"+f"(d[28]),"+f"(d[29]),"+f"(d[30]),"+f"(d[31]),"+f"(d[32]),"+f"(d[33]),"+f"(d[34]),"+f"(d[35]),"+f"(d[36]),"+f"(d[37]),"+f"(d[38]),"+f"(d[39]),"+f"(d[40]),"+f"(d[41]),"+f"(d[42]),"+f"(d[43]),"+f"(d[44]),"+f"(d[45]),"+f"(d[46]),"+f"(d[47])
    : "r"(alo), "r"(ahi), "r"(blo), "r"(bhi), "r"(sd), "n"(TA), "n"(TB)); }
  template<int TB> static __device__ __forceinline__ void rs(float* d, uint32_t a0, uint32_t a1, uint32_t a2, uint32_t a3, uint32_t blo, uint32_t bhi, int sd) {
  asm volatile("{ .reg .pred p; .reg .b64 db; mov.b64 db, {%52,%53}; setp.ne.b32 p, %55, 0;\n"
    "wgmma.mma_async.sync.aligned.m64n96k16.f32.bf16.bf16 {%0,%1,%2,%3,%4,%5,%6,%7,%8,%9,%10,%11,%12,%13,%14,%15,%16,%17,%18,%19,%20,%21,%22,%23,%24,%25,%26,%27,%28,%29,%30,%31,%32,%33,%34,%35,%36,%37,%38,%39,%40,%41,%42,%43,%44,%45,%46,%47}, {%48,%49,%50,%51}, db, p, 1, 1, %54; }"
    : "+f"(d[0]),"+f"(d[1]),"+f"(d[2]),"+f"(d[3]),"+f"(d[4]),"+f"(d[5]),"+f"(d[6]),"+f"(d[7]),"+f"(d[8]),"+f"(d[9]),"+f"(d[10]),"+f"(d[11]),"+f"(d[12]),"+f"(d[13]),"+f"(d[14]),"+f"(d[15]),"+f"(d[16]),"+f"(d[17]),"+f"(d[18]),"+f"(d[19]),"+f"(d[20]),"+f"(d[21]),"+f"(d[22]),"+f"(d[23]),"+f"(d[24]),"+f"(d[25]),"+f"(d[26]),"+f"(d[27]),"+f"(d[28]),"+f"(d[29]),"+f"(d[30]),"+f"(d[31]),"+f"(d[32]),"+f"(d[33]),"+f"(d[34]),"+f"(d[35]),"+f"(d[36]),"+f"(d[37]),"+f"(d[38]),"+f"(d[39]),"+f"(d[40]),"+f"(d[41]),"+f"(d[42]),"+f"(d[43]),"+f"(d[44]),"+f"(d[45]),"+f"(d[46]),"+f"(d[47])
    : "r"(a0), "r"(a1), "r"(a2), "r"(a3), "r"(blo), "r"(bhi), "n"(TB), "r"(sd)); }
};
template<> struct WG<112> { template<int TA, int TB> static __device__ __forceinline__ void ss(float* d, uint32_t alo, uint32_t ahi, uint32_t blo, uint32_t bhi, int sd) {
  asm volatile("{ .reg .pred p; .reg .b64 da, db; mov.b64 da, {%56,%57}; mov.b64 db, {%58,%59}; setp.ne.b32 p, %60, 0;\n"
    "wgmma.mma_async.sync.aligned.m64n112k16.f32.bf16.bf16 {%0,%1,%2,%3,%4,%5,%6,%7,%8,%9,%10,%11,%12,%13,%14,%15,%16,%17,%18,%19,%20,%21,%22,%23,%24,%25,%26,%27,%28,%29,%30,%31,%32,%33,%34,%35,%36,%37,%38,%39,%40,%41,%42,%43,%44,%45,%46,%47,%48,%49,%50,%51,%52,%53,%54,%55}, da, db, p, 1, 1, %61, %62; }"
    : "+f"(d[0]),"+f"(d[1]),"+f"(d[2]),"+f"(d[3]),"+f"(d[4]),"+f"(d[5]),"+f"(d[6]),"+f"(d[7]),"+f"(d[8]),"+f"(d[9]),"+f"(d[10]),"+f"(d[11]),"+f"(d[12]),"+f"(d[13]),"+f"(d[14]),"+f"(d[15]),"+f"(d[16]),"+f"(d[17]),"+f"(d[18]),"+f"(d[19]),"+f"(d[20]),"+f"(d[21]),"+f"(d[22]),"+f"(d[23]),"+f"(d[24]),"+f"(d[25]),"+f"(d[26]),"+f"(d[27]),"+f"(d[28]),"+f"(d[29]),"+f"(d[30]),"+f"(d[31]),"+f"(d[32]),"+f"(d[33]),"+f"(d[34]),"+f"(d[35]),"+f"(d[36]),"+f"(d[37]),"+f"(d[38]),"+f"(d[39]),"+f"(d[40]),"+f"(d[41]),"+f"(d[42]),"+f"(d[43]),"+f"(d[44]),"+f"(d[45]),"+f"(d[46]),"+f"(d[47]),"+f"(d[48]),"+f"(d[49]),"+f"(d[50]),"+f"(d[51]),"+f"(d[52]),"+f"(d[53]),"+f"(d[54]),"+f"(d[55])
    : "r"(alo), "r"(ahi), "r"(blo), "r"(bhi), "r"(sd), "n"(TA), "n"(TB)); }
  template<int TB> static __device__ __forceinline__ void rs(float* d, uint32_t a0, uint32_t a1, uint32_t a2, uint32_t a3, uint32_t blo, uint32_t bhi, int sd) {
  asm volatile("{ .reg .pred p; .reg .b64 db; mov.b64 db, {%60,%61}; setp.ne.b32 p, %63, 0;\n"
    "wgmma.mma_async.sync.aligned.m64n112k16.f32.bf16.bf16 {%0,%1,%2,%3,%4,%5,%6,%7,%8,%9,%10,%11,%12,%13,%14,%15,%16,%17,%18,%19,%20,%21,%22,%23,%24,%25,%26,%27,%28,%29,%30,%31,%32,%33,%34,%35,%36,%37,%38,%39,%40,%41,%42,%43,%44,%45,%46,%47,%48,%49,%50,%51,%52,%53,%54,%55}, {%56,%57,%58,%59}, db, p, 1, 1, %62; }"
    : "+f"(d[0]),"+f"(d[1]),"+f"(d[2]),"+f"(d[3]),"+f"(d[4]),"+f"(d[5]),"+f"(d[6]),"+f"(d[7]),"+f"(d[8]),"+f"(d[9]),"+f"(d[10]),"+f"(d[11]),"+f"(d[12]),"+f"(d[13]),"+f"(d[14]),"+f"(d[15]),"+f"(d[16]),"+f"(d[17]),"+f"(d[18]),"+f"(d[19]),"+f"(d[20]),"+f"(d[21]),"+f"(d[22]),"+f"(d[23]),"+f"(d[24]),"+f"(d[25]),"+f"(d[26]),"+f"(d[27]),"+f"(d[28]),"+f"(d[29]),"+f"(d[30]),"+f"(d[31]),"+f"(d[32]),"+f"(d[33]),"+f"(d[34]),"+f"(d[35]),"+f"(d[36]),"+f"(d[37]),"+f"(d[38]),"+f"(d[39]),"+f"(d[40]),"+f"(d[41]),"+f"(d[42]),"+f"(d[43]),"+f"(d[44]),"+f"(d[45]),"+f"(d[46]),"+f"(d[47]),"+f"(d[48]),"+f"(d[49]),"+f"(d[50]),"+f"(d[51]),"+f"(d[52]),"+f"(d[53]),"+f"(d[54]),"+f"(d[55])
    : "r"(a0), "r"(a1), "r"(a2), "r"(a3), "r"(blo), "r"(bhi), "n"(TB), "r"(sd)); }
};
template<> struct WG<128> { template<int TA, int TB> static __device__ __forceinline__ void ss(float* d, uint32_t alo, uint32_t ahi, uint32_t blo, uint32_t bhi, int sd) {
  asm volatile("{ .reg .pred p; .reg .b64 da, db; mov.b64 da, {%64,%65}; mov.b64 db, {%66,%67}; setp.ne.b32 p, %68, 0;\n"
    "wgmma.mma_async.sync.aligned.m64n128k16.f32.bf16.bf16 {%0,%1,%2,%3,%4,%5,%6,%7,%8,%9,%10,%11,%12,%13,%14,%15,%16,%17,%18,%19,%20,%21,%22,%23,%24,%25,%26,%27,%28,%29,%30,%31,%32,%33,%34,%35,%36,%37,%38,%39,%40,%41,%42,%43,%44,%45,%46,%47,%48,%49,%50,%51,%52,%53,%54,%55,%56,%57,%58,%59,%60,%61,%62,%63}, da, db, p, 1, 1, %69, %70; }"
    : "+f"(d[0]),"+f"(d[1]),"+f"(d[2]),"+f"(d[3]),"+f"(d[4]),"+f"(d[5]),"+f"(d[6]),"+f"(d[7]),"+f"(d[8]),"+f"(d[9]),"+f"(d[10]),"+f"(d[11]),"+f"(d[12]),"+f"(d[13]),"+f"(d[14]),"+f"(d[15]),"+f"(d[16]),"+f"(d[17]),"+f"(d[18]),"+f"(d[19]),"+f"(d[20]),"+f"(d[21]),"+f"(d[22]),"+f"(d[23]),"+f"(d[24]),"+f"(d[25]),"+f"(d[26]),"+f"(d[27]),"+f"(d[28]),"+f"(d[29]),"+f"(d[30]),"+f"(d[31]),"+f"(d[32]),"+f"(d[33]),"+f"(d[34]),"+f"(d[35]),"+f"(d[36]),"+f"(d[37]),"+f"(d[38]),"+f"(d[39]),"+f"(d[40]),"+f"(d[41]),"+f"(d[42]),"+f"(d[43]),"+f"(d[44]),"+f"(d[45]),"+f"(d[46]),"+f"(d[47]),"+f"(d[48]),"+f"(d[49]),"+f"(d[50]),"+f"(d[51]),"+f"(d[52]),"+f"(d[53]),"+f"(d[54]),"+f"(d[55]),"+f"(d[56]),"+f"(d[57]),"+f"(d[58]),"+f"(d[59]),"+f"(d[60]),"+f"(d[61]),"+f"(d[62]),"+f"(d[63])
    : "r"(alo), "r"(ahi), "r"(blo), "r"(bhi), "r"(sd), "n"(TA), "n"(TB)); }
  template<int TB> static __device__ __forceinline__ void rs(float* d, uint32_t a0, uint32_t a1, uint32_t a2, uint32_t a3, uint32_t blo, uint32_t bhi, int sd) {
  asm volatile("{ .reg .pred p; .reg .b64 db; mov.b64 db, {%68,%69}; setp.ne.b32 p, %71, 0;\n"
    "wgmma.mma_async.sync.aligned.m64n128k16.f32.bf16.bf16 {%0,%1,%2,%3,%4,%5,%6,%7,%8,%9,%10,%11,%12,%13,%14,%15,%16,%17,%18,%19,%20,%21,%22,%23,%24,%25,%26,%27,%28,%29,%30,%31,%32,%33,%34,%35,%36,%37,%38,%39,%40,%41,%42,%43,%44,%45,%46,%47,%48,%49,%50,%51,%52,%53,%54,%55,%56,%57,%58,%59,%60,%61,%62,%63}, {%64,%65,%66,%67}, db, p, 1, 1, %70; }"
    : "+f"(d[0]),"+f"(d[1]),"+f"(d[2]),"+f"(d[3]),"+f"(d[4]),"+f"(d[5]),"+f"(d[6]),"+f"(d[7]),"+f"(d[8]),"+f"(d[9]),"+f"(d[10]),"+f"(d[11]),"+f"(d[12]),"+f"(d[13]),"+f"(d[14]),"+f"(d[15]),"+f"(d[16]),"+f"(d[17]),"+f"(d[18]),"+f"(d[19]),"+f"(d[20]),"+f"(d[21]),"+f"(d[22]),"+f"(d[23]),"+f"(d[24]),"+f"(d[25]),"+f"(d[26]),"+f"(d[27]),"+f"(d[28]),"+f"(d[29]),"+f"(d[30]),"+f"(d[31]),"+f"(d[32]),"+f"(d[33]),"+f"(d[34]),"+f"(d[35]),"+f"(d[36]),"+f"(d[37]),"+f"(d[38]),"+f"(d[39]),"+f"(d[40]),"+f"(d[41]),"+f"(d[42]),"+f"(d[43]),"+f"(d[44]),"+f"(d[45]),"+f"(d[46]),"+f"(d[47]),"+f"(d[48]),"+f"(d[49]),"+f"(d[50]),"+f"(d[51]),"+f"(d[52]),"+f"(d[53]),"+f"(d[54]),"+f"(d[55]),"+f"(d[56]),"+f"(d[57]),"+f"(d[58]),"+f"(d[59]),"+f"(d[60]),"+f"(d[61]),"+f"(d[62]),"+f"(d[63])
    : "r"(a0), "r"(a1), "r"(a2), "r"(a3), "r"(blo), "r"(bhi), "n"(TB), "r"(sd)); }
};
template<> struct WG<144> { template<int TA, int TB> static __device__ __forceinline__ void ss(float* d, uint32_t alo, uint32_t ahi, uint32_t blo, uint32_t bhi, int sd) {
  asm volatile("{ .reg .pred p; .reg .b64 da, db; mov.b64 da, {%72,%73}; mov.b64 db, {%74,%75}; setp.ne.b32 p, %76, 0;\n"
    "wgmma.mma_async.sync.aligned.m64n144k16.f32.bf16.bf16 {%0,%1,%2,%3,%4,%5,%6,%7,%8,%9,%10,%11,%12,%13,%14,%15,%16,%17,%18,%19,%20,%21,%22,%23,%24,%25,%26,%27,%28,%29,%30,%31,%32,%33,%34,%35,%36,%37,%38,%39,%40,%41,%42,%43,%44,%45,%46,%47,%48,%49,%50,%51,%52,%53,%54,%55,%56,%57,%58,%59,%60,%61,%62,%63,%64,%65,%66,%67,%68,%69,%70,%71}, da, db, p, 1, 1, %77, %78; }"
    : "+f"(d[0]),"+f"(d[1]),"+f"(d[2]),"+f"(d[3]),"+f"(d[4]),"+f"(d[5]),"+f"(d[6]),"+f"(d[7]),"+f"(d[8]),"+f"(d[9]),"+f"(d[10]),"+f"(d[11]),"+f"(d[12]),"+f"(d[13]),"+f"(d[14]),"+f"(d[15]),"+f"(d[16]),"+f"(d[17]),"+f"(d[18]),"+f"(d[19]),"+f"(d[20]),"+f"(d[21]),"+f"(d[22]),"+f"(d[23]),"+f"(d[24]),"+f"(d[25]),"+f"(d[26]),"+f"(d[27]),"+f"(d[28]),"+f"(d[29]),"+f"(d[30]),"+f"(d[31]),"+f"(d[32]),"+f"(d[33]),"+f"(d[34]),"+f"(d[35]),"+f"(d[36]),"+f"(d[37]),"+f"(d[38]),"+f"(d[39]),"+f"(d[40]),"+f"(d[41]),"+f"(d[42]),"+f"(d[43]),"+f"(d[44]),"+f"(d[45]),"+f"(d[46]),"+f"(d[47]),"+f"(d[48]),"+f"(d[49]),"+f"(d[50]),"+f"(d[51]),"+f"(d[52]),"+f"(d[53]),"+f"(d[54]),"+f"(d[55]),"+f"(d[56]),"+f"(d[57]),"+f"(d[58]),"+f"(d[59]),"+f"(d[60]),"+f"(d[61]),"+f"(d[62]),"+f"(d[63]),"+f"(d[64]),"+f"(d[65]),"+f"(d[66]),"+f"(d[67]),"+f"(d[68]),"+f"(d[69]),"+f"(d[70]),"+f"(d[71])
    : "r"(alo), "r"(ahi), "r"(blo), "r"(bhi), "r"(sd), "n"(TA), "n"(TB)); }
  template<int TB> static __device__ __forceinline__ void rs(float* d, uint32_t a0, uint32_t a1, uint32_t a2, uint32_t a3, uint32_t blo, uint32_t bhi, int sd) {
  asm volatile("{ .reg .pred p; .reg .b64 db; mov.b64 db, {%76,%77}; setp.ne.b32 p, %79, 0;\n"
    "wgmma.mma_async.sync.aligned.m64n144k16.f32.bf16.bf16 {%0,%1,%2,%3,%4,%5,%6,%7,%8,%9,%10,%11,%12,%13,%14,%15,%16,%17,%18,%19,%20,%21,%22,%23,%24,%25,%26,%27,%28,%29,%30,%31,%32,%33,%34,%35,%36,%37,%38,%39,%40,%41,%42,%43,%44,%45,%46,%47,%48,%49,%50,%51,%52,%53,%54,%55,%56,%57,%58,%59,%60,%61,%62,%63,%64,%65,%66,%67,%68,%69,%70,%71}, {%72,%73,%74,%75}, db, p, 1, 1, %78; }"
    : "+f"(d[0]),"+f"(d[1]),"+f"(d[2]),"+f"(d[3]),"+f"(d[4]),"+f"(d[5]),"+f"(d[6]),"+f"(d[7]),"+f"(d[8]),"+f"(d[9]),"+f"(d[10]),"+f"(d[11]),"+f"(d[12]),"+f"(d[13]),"+f"(d[14]),"+f"(d[15]),"+f"(d[16]),"+f"(d[17]),"+f"(d[18]),"+f"(d[19]),"+f"(d[20]),"+f"(d[21]),"+f"(d[22]),"+f"(d[23]),"+f"(d[24]),"+f"(d[25]),"+f"(d[26]),"+f"(d[27]),"+f"(d[28]),"+f"(d[29]),"+f"(d[30]),"+f"(d[31]),"+f"(d[32]),"+f"(d[33]),"+f"(d[34]),"+f"(d[35]),"+f"(d[36]),"+f"(d[37]),"+f"(d[38]),"+f"(d[39]),"+f"(d[40]),"+f"(d[41]),"+f"(d[42]),"+f"(d[43]),"+f"(d[44]),"+f"(d[45]),"+f"(d[46]),"+f"(d[47]),"+f"(d[48]),"+f"(d[49]),"+f"(d[50]),"+f"(d[51]),"+f"(d[52]),"+f"(d[53]),"+f"(d[54]),"+f"(d[55]),"+f"(d[56]),"+f"(d[57]),"+f"(d[58]),"+f"(d[59]),"+f"(d[60]),"+f"(d[61]),"+f"(d[62]),"+f"(d[63]),"+f"(d[64]),"+f"(d[65]),"+f"(d[66]),"+f"(d[67]),"+f"(d[68]),"+f"(d[69]),"+f"(d[70]),"+f"(d[71])
    : "r"(a0), "r"(a1), "r"(a2), "r"(a3), "r"(blo), "r"(bhi), "n"(TB), "r"(sd)); }
};
template<> struct WG<160> { template<int TA, int TB> static __device__ __forceinline__ void ss(float* d, uint32_t alo, uint32_t ahi, uint32_t blo, uint32_t bhi, int sd) {
  asm volatile("{ .reg .pred p; .reg .b64 da, db; mov.b64 da, {%80,%81}; mov.b64 db, {%82,%83}; setp.ne.b32 p, %84, 0;\n"
    "wgmma.mma_async.sync.aligned.m64n160k16.f32.bf16.bf16 {%0,%1,%2,%3,%4,%5,%6,%7,%8,%9,%10,%11,%12,%13,%14,%15,%16,%17,%18,%19,%20,%21,%22,%23,%24,%25,%26,%27,%28,%29,%30,%31,%32,%33,%34,%35,%36,%37,%38,%39,%40,%41,%42,%43,%44,%45,%46,%47,%48,%49,%50,%51,%52,%53,%54,%55,%56,%57,%58,%59,%60,%61,%62,%63,%64,%65,%66,%67,%68,%69,%70,%71,%72,%73,%74,%75,%76,%77,%78,%79}, da, db, p, 1, 1, %85, %86; }"
    : "+f"(d[0]),"+f"(d[1]),"+f"(d[2]),"+f"(d[3]),"+f"(d[4]),"+f"(d[5]),"+f"(d[6]),"+f"(d[7]),"+f"(d[8]),"+f"(d[9]),"+f"(d[10]),"+f"(d[11]),"+f"(d[12]),"+f"(d[13]),"+f"(d[14]),"+f"(d[15]),"+f"(d[16]),"+f"(d[17]),"+f"(d[18]),"+f"(d[19]),"+f"(d[20]),"+f"(d[21]),"+f"(d[22]),"+f"(d[23]),"+f"(d[24]),"+f"(d[25]),"+f"(d[26]),"+f"(d[27]),"+f"(d[28]),"+f"(d[29]),"+f"(d[30]),"+f"(d[31]),"+f"(d[32]),"+f"(d[33]),"+f"(d[34]),"+f"(d[35]),"+f"(d[36]),"+f"(d[37]),"+f"(d[38]),"+f"(d[39]),"+f"(d[40]),"+f"(d[41]),"+f"(d[42]),"+f"(d[43]),"+f"(d[44]),"+f"(d[45]),"+f"(d[46]),"+f"(d[47]),"+f"(d[48]),"+f"(d[49]),"+f"(d[50]),"+f"(d[51]),"+f"(d[52]),"+f"(d[53]),"+f"(d[54]),"+f"(d[55]),"+f"(d[56]),"+f"(d[57]),"+f"(d[58]),"+f"(d[59]),"+f"(d[60]),"+f"(d[61]),"+f"(d[62]),"+f"(d[63]),"+f"(d[64]),"+f"(d[65]),"+f"(d[66]),"+f"(d[67]),"+f"(d[68]),"+f"(d[69]),"+f"(d[70]),"+f"(d[71]),"+f"(d[72]),"+f"(d[73]),"+f"(d[74]),"+f"(d[75]),"+f"(d[76]),"+f"(d[77]),"+f"(d[78]),"+f"(d[79])
    : "r"(alo), "r"(ahi), "r"(blo), "r"(bhi), "r"(sd), "n"(TA), "n"(TB)); }
  template<int TB> static __device__ __forceinline__ void rs(float* d, uint32_t a0, uint32_t a1, uint32_t a2, uint32_t a3, uint32_t blo, uint32_t bhi, int sd) {
  asm volatile("{ .reg .pred p; .reg .b64 db; mov.b64 db, {%84,%85}; setp.ne.b32 p, %87, 0;\n"
    "wgmma.mma_async.sync.aligned.m64n160k16.f32.bf16.bf16 {%0,%1,%2,%3,%4,%5,%6,%7,%8,%9,%10,%11,%12,%13,%14,%15,%16,%17,%18,%19,%20,%21,%22,%23,%24,%25,%26,%27,%28,%29,%30,%31,%32,%33,%34,%35,%36,%37,%38,%39,%40,%41,%42,%43,%44,%45,%46,%47,%48,%49,%50,%51,%52,%53,%54,%55,%56,%57,%58,%59,%60,%61,%62,%63,%64,%65,%66,%67,%68,%69,%70,%71,%72,%73,%74,%75,%76,%77,%78,%79}, {%80,%81,%82,%83}, db, p, 1, 1, %86; }"
    : "+f"(d[0]),"+f"(d[1]),"+f"(d[2]),"+f"(d[3]),"+f"(d[4]),"+f"(d[5]),"+f"(d[6]),"+f"(d[7]),"+f"(d[8]),"+f"(d[9]),"+f"(d[10]),"+f"(d[11]),"+f"(d[12]),"+f"(d[13]),"+f"(d[14]),"+f"(d[15]),"+f"(d[16]),"+f"(d[17]),"+f"(d[18]),"+f"(d[19]),"+f"(d[20]),"+f"(d[21]),"+f"(d[22]),"+f"(d[23]),"+f"(d[24]),"+f"(d[25]),"+f"(d[26]),"+f"(d[27]),"+f"(d[28]),"+f"(d[29]),"+f"(d[30]),"+f"(d[31]),"+f"(d[32]),"+f"(d[33]),"+f"(d[34]),"+f"(d[35]),"+f"(d[36]),"+f"(d[37]),"+f"(d[38]),"+f"(d[39]),"+f"(d[40]),"+f"(d[41]),"+f"(d[42]),"+f"(d[43]),"+f"(d[44]),"+f"(d[45]),"+f"(d[46]),"+f"(d[47]),"+f"(d[48]),"+f"(d[49]),"+f"(d[50]),"+f"(d[51]),"+f"(d[52]),"+f"(d[53]),"+f"(d[54]),"+f"(d[55]),"+f"(d[56]),"+f"(d[57]),"+f"(d[58]),"+f"(d[59]),"+f"(d[60]),"+f"(d[61]),"+f"(d[62]),"+f"(d[63]),"+f"(d[64]),"+f"(d[65]),"+f"(d[66]),"+f"(d[67]),"+f"(d[68]),"+f"(d[69]),"+f"(d[70]),"+f"(d[71]),"+f"(d[72]),"+f"(d[73]),"+f"(d[74]),"+f"(d[75]),"+f"(d[76]),"+f"(d[77]),"+f"(d[78]),"+f"(d[79])
    : "r"(a0), "r"(a1), "r"(a2), "r"(a3), "r"(blo), "r"(bhi), "n"(TB), "r"(sd)); }
};
template<> struct WG<176> { template<int TA, int TB> static __device__ __forceinline__ void ss(float* d, uint32_t alo, uint32_t ahi, uint32_t blo, uint32_t bhi, int sd) {
  asm volatile("{ .reg .pred p; .reg .b64 da, db; mov.b64 da, {%88,%89}; mov.b64 db, {%90,%91}; setp.ne.b32 p, %92, 0;\n"
    "wgmma.mma_async.sync.aligned.m64n176k16.f32.bf16.bf16 {%0,%1,%2,%3,%4,%5,%6,%7,%8,%9,%10,%11,%12,%13,%14,%15,%16,%17,%18,%19,%20,%21,%22,%23,%24,%25,%26,%27,%28,%29,%30,%31,%32,%33,%34,%35,%36,%37,%38,%39,%40,%41,%42,%43,%44,%45,%46,%47,%48,%49,%50,%51,%52,%53,%54,%55,%56,%57,%58,%59,%60,%61,%62,%63,%64,%65,%66,%67,%68,%69,%70,%71,%72,%73,%74,%75,%76,%77,%78,%79,%80,%81,%82,%83,%84,%85,%86,%87}, da, db, p, 1, 1, %93, %94; }"
    : "+f"(d[0]),"+f"(d[1]),"+f"(d[2]),"+f"(d[3]),"+f"(d[4]),"+f"(d[5]),"+f"(d[6]),"+f"(d[7]),"+f"(d[8]),"+f"(d[9]),"+f"(d[10]),"+f"(d[11]),"+f"(d[12]),"+f"(d[13]),"+f"(d[14]),"+f"(d[15]),"+f"(d[16]),"+f"(d[17]),"+f"(d[18]),"+f"(d[19]),"+f"(d[20]),"+f"(d[21]),"+f"(d[22]),"+f"(d[23]),"+f"(d[24]),"+f"(d[25]),"+f"(d[26]),"+f"(d[27]),"+f"(d[28]),"+f"(d[29]),"+f"(d[30]),"+f"(d[31]),"+f"(d[32]),"+f"(d[33]),"+f"(d[34]),"+f"(d[35]),"+f"(d[36]),"+f"(d[37]),"+f"(d[38]),"+f"(d[39]),"+f"(d[40]),"+f"(d[41]),"+f"(d[42]),"+f"(d[43]),"+f"(d[44]),"+f"(d[45]),"+f"(d[46]),"+f"(d[47]),"+f"(d[48]),"+f"(d[49]),"+f"(d[50]),"+f"(d[51]),"+f"(d[52]),"+f"(d[53]),"+f"(d[54]),"+f"(d[55]),"+f"(d[56]),"+f"(d[57]),"+f"(d[58]),"+f"(d[59]),"+f"(d[60]),"+f"(d[61]),"+f"(d[62]),"+f"(d[63]),"+f"(d[64]),"+f"(d[65]),"+f"(d[66]),"+f"(d[67]),"+f"(d[68]),"+f"(d[69]),"+f"(d[70]),"+f"(d[71]),"+f"(d[72]),"+f"(d[73]),"+f"(d[74]),"+f"(d[75]),"+f"(d[76]),"+f"(d[77]),"+f"(d[78]),"+f"(d[79]),"+f"(d[80]),"+f"(d[81]),"+f"(d[82]),"+f"(d[83]),"+f"(d[84]),"+f"(d[85]),"+f"(d[86]),"+f"(d[87])
    : "r"(alo), "r"(ahi), "r"(blo), "r"(bhi), "r"(sd), "n"(TA), "n"(TB)); }
  template<int TB> static __device__ __forceinline__ void rs(float* d, uint32_t a0, uint32_t a1, uint32_t a2, uint32_t a3, uint32_t blo, uint32_t bhi, int sd) {
  asm volatile("{ .reg .pred p; .reg .b64 db; mov.b64 db, {%92,%93}; setp.ne.b32 p, %95, 0;\n"
    "wgmma.mma_async.sync.aligned.m64n176k16.f32.bf16.bf16 {%0,%1,%2,%3,%4,%5,%6,%7,%8,%9,%10,%11,%12,%13,%14,%15,%16,%17,%18,%19,%20,%21,%22,%23,%24,%25,%26,%27,%28,%29,%30,%31,%32,%33,%34,%35,%36,%37,%38,%39,%40,%41,%42,%43,%44,%45,%46,%47,%48,%49,%50,%51,%52,%53,%54,%55,%56,%57,%58,%59,%60,%61,%62,%63,%64,%65,%66,%67,%68,%69,%70,%71,%72,%73,%74,%75,%76,%77,%78,%79,%80,%81,%82,%83,%84,%85,%86,%87}, {%88,%89,%90,%91}, db, p, 1, 1, %94; }"
    : "+f"(d[0]),"+f"(d[1]),"+f"(d[2]),"+f"(d[3]),"+f"(d[4]),"+f"(d[5]),"+f"(d[6]),"+f"(d[7]),"+f"(d[8]),"+f"(d[9]),"+f"(d[10]),"+f"(d[11]),"+f"(d[12]),"+f"(d[13]),"+f"(d[14]),"+f"(d[15]),"+f"(d[16]),"+f"(d[17]),"+f"(d[18]),"+f"(d[19]),"+f"(d[20]),"+f"(d[21]),"+f"(d[22]),"+f"(d[23]),"+f"(d[24]),"+f"(d[25]),"+f"(d[26]),"+f"(d[27]),"+f"(d[28]),"+f"(d[29]),"+f"(d[30]),"+f"(d[31]),"+f"(d[32]),"+f"(d[33]),"+f"(d[34]),"+f"(d[35]),"+f"(d[36]),"+f"(d[37]),"+f"(d[38]),"+f"(d[39]),"+f"(d[40]),"+f"(d[41]),"+f"(d[42]),"+f"(d[43]),"+f"(d[44]),"+f"(d[45]),"+f"(d[46]),"+f"(d[47]),"+f"(d[48]),"+f"(d[49]),"+f"(d[50]),"+f"(d[51]),"+f"(d[52]),"+f"(d[53]),"+f"(d[54]),"+f"(d[55]),"+f"(d[56]),"+f"(d[57]),"+f"(d[58]),"+f"(d[59]),"+f"(d[60]),"+f"(d[61]),"+f"(d[62]),"+f"(d[63]),"+f"(d[64]),"+f"(d[65]),"+f"(d[66]),"+f"(d[67]),"+f"(d[68]),"+f"(d[69]),"+f"(d[70]),"+f"(d[71]),"+f"(d[72]),"+f"(d[73]),"+f"(d[74]),"+f"(d[75]),"+f"(d[76]),"+f"(d[77]),"+f"(d[78]),"+f"(d[79]),"+f"(d[80]),"+f"(d[81]),"+f"(d[82]),"+f"(d[83]),"+f"(d[84]),"+f"(d[85]),"+f"(d[86]),"+f"(d[87])
    : "r"(a0), "r"(a1), "r"(a2), "r"(a3), "r"(blo), "r"(bhi), "n"(TB), "r"(sd)); }
};
template<> struct WG<192> { template<int TA, int TB> static __device__ __forceinline__ void ss(float* d, uint32_t alo, uint32_t ahi, uint32_t blo, uint32_t bhi, int sd) {
  asm volatile("{ .reg .pred p; .reg .b64 da, db; mov.b64 da, {%96,%97}; mov.b64 db, {%98,%99}; setp.ne.b32 p, %100, 0;\n"
    "wgmma.mma_async.sync.aligned.m64n192k16.f32.bf16.bf16 {%0,%1,%2,%3,%4,%5,%6,%7,%8,%9,%10,%11,%12,%13,%14,%15,%16,%17,%18,%19,%20,%21,%22,%23,%24,%25,%26,%27,%28,%29,%30,%31,%32,%33,%34,%35,%36,%37,%38,%39,%40,%41,%42,%43,%44,%45,%46,%47,%48,%49,%50,%51,%52,%53,%54,%55,%56,%57,%58,%59,%60,%61,%62,%63,%64,%65,%66,%67,%68,%69,%70,%71,%72,%73,%74,%75,%76,%77,%78,%79,%80,%81,%82,%83,%84,%85,%86,%87,%88,%89,%90,%91,%92,%93,%94,%95}, da, db, p, 1, 1, %101, %102; }"
    : "+f"(d[0]),"+f"(d[1]),"+f"(d[2]),"+f"(d[3]),"+f"(d[4]),"+f"(d[5]),"+f"(d[6]),"+f"(d[7]),"+f"(d[8]),"+f"(d[9]),"+f"(d[10]),"+f"(d[11]),"+f"(d[12]),"+f"(d[13]),"+f"(d[14]),"+f"(d[15]),"+f"(d[16]),"+f"(d[17]),"+f"(d[18]),"+f"(d[19]),"+f"(d[20]),"+f"(d[21]),"+f"(d[22]),"+f"(d[23]),"+f"(d[24]),"+f"(d[25]),"+f"(d[26]),"+f"(d[27]),"+f"(d[28]),"+f"(d[29]),"+f"(d[30]),"+f"(d[31]),"+f"(d[32]),"+f"(d[33]),"+f"(d[34]),"+f"(d[35]),"+f"(d[36]),"+f"(d[37]),"+f"(d[38]),"+f"(d[39]),"+f"(d[40]),"+f"(d[41]),"+f"(d[42]),"+f"(d[43]),"+f"(d[44]),"+f"(d[45]),"+f"(d[46]),"+f"(d[47]),"+f"(d[48]),"+f"(d[49]),"+f"(d[50]),"+f"(d[51]),"+f"(d[52]),"+f"(d[53]),"+f"(d[54]),"+f"(d[55]),"+f"(d[56]),"+f"(d[57]),"+f"(d[58]),"+f"(d[59]),"+f"(d[60]),"+f"(d[61]),"+f"(d[62]),"+f"(d[63]),"+f"(d[64]),"+f"(d[65]),"+f"(d[66]),"+f"(d[67]),"+f"(d[68]),"+f"(d[69]),"+f"(d[70]),"+f"(d[71]),"+f"(d[72]),"+f"(d[73]),"+f"(d[74]),"+f"(d[75]),"+f"(d[76]),"+f"(d[77]),"+f"(d[78]),"+f"(d[79]),"+f"(d[80]),"+f"(d[81]),"+f"(d[82]),"+f"(d[83]),"+f"(d[84]),"+f"(d[85]),"+f"(d[86]),"+f"(d[87]),"+f"(d[88]),"+f"(d[89]),"+f"(d[90]),"+f"(d[91]),"+f"(d[92]),"+f"(d[93]),"+f"(d[94]),"+f"(d[95])
    : "r"(alo), "r"(ahi), "r"(blo), "r"(bhi), "r"(sd), "n"(TA), "n"(TB)); }
  template<int TB> static __device__ __forceinline__ void rs(float* d, uint32_t a0, uint32_t a1, uint32_t a2, uint32_t a3, uint32_t blo, uint32_t bhi, int sd) {
  asm volatile("{ .reg .pred p; .reg .b64 db; mov.b64 db, {%100,%101}; setp.ne.b32 p, %103, 0;\n"
    "wgmma.mma_async.sync.aligned.m64n192k16.f32.bf16.bf16 {%0,%1,%2,%3,%4,%5,%6,%7,%8,%9,%10,%11,%12,%13,%14,%15,%16,%17,%18,%19,%20,%21,%22,%23,%24,%25,%26,%27,%28,%29,%30,%31,%32,%33,%34,%35,%36,%37,%38,%39,%40,%41,%42,%43,%44,%45,%46,%47,%48,%49,%50,%51,%52,%53,%54,%55,%56,%57,%58,%59,%60,%61,%62,%63,%64,%65,%66,%67,%68,%69,%70,%71,%72,%73,%74,%75,%76,%77,%78,%79,%80,%81,%82,%83,%84,%85,%86,%87,%88,%89,%90,%91,%92,%93,%94,%95}, {%96,%97,%98,%99}, db, p, 1, 1, %102; }"
    : "+f"(d[0]),"+f"(d[1]),"+f"(d[2]),"+f"(d[3]),"+f"(d[4]),"+f"(d[5]),"+f"(d[6]),"+f"(d[7]),"+f"(d[8]),"+f"(d[9]),"+f"(d[10]),"+f"(d[11]),"+f"(d[12]),"+f"(d[13]),"+f"(d[14]),"+f"(d[15]),"+f"(d[16]),"+f"(d[17]),"+f"(d[18]),"+f"(d[19]),"+f"(d[20]),"+f"(d[21]),"+f"(d[22]),"+f"(d[23]),"+f"(d[24]),"+f"(d[25]),"+f"(d[26]),"+f"(d[27]),"+f"(d[28]),"+f"(d[29]),"+f"(d[30]),"+f"(d[31]),"+f"(d[32]),"+f"(d[33]),"+f"(d[34]),"+f"(d[35]),"+f"(d[36]),"+f"(d[37]),"+f"(d[38]),"+f"(d[39]),"+f"(d[40]),"+f"(d[41]),"+f"(d[42]),"+f"(d[43]),"+f"(d[44]),"+f"(d[45]),"+f"(d[46]),"+f"(d[47]),"+f"(d[48]),"+f"(d[49]),"+f"(d[50]),"+f"(d[51]),"+f"(d[52]),"+f"(d[53]),"+f"(d[54]),"+f"(d[55]),"+f"(d[56]),"+f"(d[57]),"+f"(d[58]),"+f"(d[59]),"+f"(d[60]),"+f"(d[61]),"+f"(d[62]),"+f"(d[63]),"+f"(d[64]),"+f"(d[65]),"+f"(d[66]),"+f"(d[67]),"+f"(d[68]),"+f"(d[69]),"+f"(d[70]),"+f"(d[71]),"+f"(d[72]),"+f"(d[73]),"+f"(d[74]),"+f"(d[75]),"+f"(d[76]),"+f"(d[77]),"+f"(d[78]),"+f"(d[79]),"+f"(d[80]),"+f"(d[81]),"+f"(d[82]),"+f"(d[83]),"+f"(d[84]),"+f"(d[85]),"+f"(d[86]),"+f"(d[87]),"+f"(d[88]),"+f"(d[89]),"+f"(d[90]),"+f"(d[91]),"+f"(d[92]),"+f"(d[93]),"+f"(d[94]),"+f"(d[95])
    : "r"(a0), "r"(a1), "r"(a2), "r"(a3), "r"(blo), "r"(bhi), "n"(TB), "r"(sd)); }
};
template<> struct WG<208> { template<int TA, int TB> static __device__ __forceinline__ void ss(float* d, uint32_t alo, uint32_t ahi, uint32_t blo, uint32_t bhi, int sd) {
  asm volatile("{ .reg .pred p; .reg .b64 da, db; mov.b64 da, {%104,%105}; mov.b64 db, {%106,%107}; setp.ne.b32 p, %108, 0;\n"
    "wgmma.mma_async.sync.aligned.m64n208k16.f32.bf16.bf16 {%0,%1,%2,%3,%4,%5,%6,%7,%8,%9,%10,%11,%12,%13,%14,%15,%16,%17,%18,%19,%20,%21,%22,%23,%24,%25,%26,%27,%28,%29,%30,%31,%32,%33,%34,%35,%36,%37,%38,%39,%40,%41,%42,%43,%44,%45,%46,%47,%48,%49,%50,%51,%52,%53,%54,%55,%56,%57,%58,%59,%60,%61,%62,%63,%64,%65,%66,%67,%68,%69,%70,%71,%72,%73,%74,%75,%76,%77,%78,%79,%80,%81,%82,%83,%84,%85,%86,%87,%88,%89,%90,%91,%92,%93,%94,%95,%96,%97,%98,%99,%100,%101,%102,%103}, da, db, p, 1, 1, %109, %110; }"
    : "+f"(d[0]),"+f"(d[1]),"+f"(d[2]),"+f"(d[3]),"+f"(d[4]),"+f"(d[5]),"+f"(d[6]),"+f"(d[7]),"+f"(d[8]),"+f"(d[9]),"+f"(d[10]),"+f"(d[11]),"+f"(d[12]),"+f"(d[13]),"+f"(d[14]),"+f"(d[15]),"+f"(d[16]),"+f"(d[17]),"+f"(d[18]),"+f"(d[19]),"+f"(d[20]),"+f"(d[21]),"+f"(d[22]),"+f"(d[23]),"+f"(d[24]),"+f"(d[25]),"+f"(d[26]),"+f"(d[27]),"+f"(d[28]),"+f"(d[29]),"+f"(d[30]),"+f"(d[31]),"+f"(d[32]),"+f"(d[33]),"+f"(d[34]),"+f"(d[35]),"+f"(d[36]),"+f"(d[37]),"+f"(d[38]),"+f"(d[39]),"+f"(d[40]),"+f"(d[41]),"+f"(d[42]),"+f"(d[43]),"+f"(d[44]),"+f"(d[45]),"+f"(d[46]),"+f"(d[47]),"+f"(d[48]),"+f"(d[49]),"+f"(d[50]),"+f"(d[51]),"+f"(d[52]),"+f"(d[53]),"+f"(d[54]),"+f"(d[55]),"+f"(d[56]),"+f"(d[57]),"+f"(d[58]),"+f"(d[59]),"+f"(d[60]),"+f"(d[61]),"+f"(d[62]),"+f"(d[63]),"+f"(d[64]),"+f"(d[65]),"+f"(d[66]),"+f"(d[67]),"+f"(d[68]),"+f"(d[69]),"+f"(d[70]),"+f"(d[71]),"+f"(d[72]),"+f"(d[73]),"+f"(d[74]),"+f"(d[75]),"+f"(d[76]),"+f"(d[77]),"+f"(d[78]),"+f"(d[79]),"+f"(d[80]),"+f"(d[81]),"+f"(d[82]),"+f"(d[83]),"+f"(d[84]),"+f"(d[85]),"+f"(d[86]),"+f"(d[87]),"+f"(d[88]),"+f"(d[89]),"+f"(d[90]),"+f"(d[91]),"+f"(d[92]),"+f"(d[93]),"+f"(d[94]),"+f"(d[95]),"+f"(d[96]),"+f"(d[97]),"+f"(d[98]),"+f"(d[99]),"+f"(d[100]),"+f"(d[101]),"+f"(d[102]),"+f"(d[103])
    : "r"(alo), "r"(ahi), "r"(blo), "r"(bhi), "r"(sd), "n"(TA), "n"(TB)); }
  template<int TB> static __device__ __forceinline__ void rs(float* d, uint32_t a0, uint32_t a1, uint32_t a2, uint32_t a3, uint32_t blo, uint32_t bhi, int sd) {
  asm volatile("{ .reg .pred p; .reg .b64 db; mov.b64 db, {%108,%109}; setp.ne.b32 p, %111, 0;\n"
    "wgmma.mma_async.sync.aligned.m64n208k16.f32.bf16.bf16 {%0,%1,%2,%3,%4,%5,%6,%7,%8,%9,%10,%11,%12,%13,%14,%15,%16,%17,%18,%19,%20,%21,%22,%23,%24,%25,%26,%27,%28,%29,%30,%31,%32,%33,%34,%35,%36,%37,%38,%39,%40,%41,%42,%43,%44,%45,%46,%47,%48,%49,%50,%51,%52,%53,%54,%55,%56,%57,%58,%59,%60,%61,%62,%63,%64,%65,%66,%67,%68,%69,%70,%71,%72,%73,%74,%75,%76,%77,%78,%79,%80,%81,%82,%83,%84,%85,%86,%87,%88,%89,%90,%91,%92,%93,%94,%95,%96,%97,%98,%99,%100,%101,%102,%103}, {%104,%105,%106,%107}, db, p, 1, 1, %110; }"
    : "+f"(d[0]),"+f"(d[1]),"+f"(d[2]),"+f"(d[3]),"+f"(d[4]),"+f"(d[5]),"+f"(d[6]),"+f"(d[7]),"+f"(d[8]),"+f"(d[9]),"+f"(d[10]),"+f"(d[11]),"+f"(d[12]),"+f"(d[13]),"+f"(d[14]),"+f"(d[15]),"+f"(d[16]),"+f"(d[17]),"+f"(d[18]),"+f"(d[19]),"+f"(d[20]),"+f"(d[21]),"+f"(d[22]),"+f"(d[23]),"+f"(d[24]),"+f"(d[25]),"+f"(d[26]),"+f"(d[27]),"+f"(d[28]),"+f"(d[29]),"+f"(d[30]),"+f"(d[31]),"+f"(d[32]),"+f"(d[33]),"+f"(d[34]),"+f"(d[35]),"+f"(d[36]),"+f"(d[37]),"+f"(d[38]),"+f"(d[39]),"+f"(d[40]),"+f"(d[41]),"+f"(d[42]),"+f"(d[43]),"+f"(d[44]),"+f"(d[45]),"+f"(d[46]),"+f"(d[47]),"+f"(d[48]),"+f"(d[49]),"+f"(d[50]),"+f"(d[51]),"+f"(d[52]),"+f"(d[53]),"+f"(d[54]),"+f"(d[55]),"+f"(d[56]),"+f"(d[57]),"+f"(d[58]),"+f"(d[59]),"+f"(d[60]),"+f"(d[61]),"+f"(d[62]),"+f"(d[63]),"+f"(d[64]),"+f"(d[65]),"+f"(d[66]),"+f"(d[67]),"+f"(d[68]),"+f"(d[69]),"+f"(d[70]),"+f"(d[71]),"+f"(d[72]),"+f"(d[73]),"+f"(d[74]),"+f"(d[75]),"+f"(d[76]),"+f"(d[77]),"+f"(d[78]),"+f"(d[79]),"+f"(d[80]),"+f"(d[81]),"+f"(d[82]),"+f"(d[83]),"+f"(d[84]),"+f"(d[85]),"+f"(d[86]),"+f"(d[87]),"+f"(d[88]),"+f"(d[89]),"+f"(d[90]),"+f"(d[91]),"+f"(d[92]),"+f"(d[93]),"+f"(d[94]),"+f"(d[95]),"+f"(d[96]),"+f"(d[97]),"+f"(d[98]),"+f"(d[99]),"+f"(d[100]),"+f"(d[101]),"+f"(d[102]),"+f"(d[103])
    : "r"(a0), "r"(a1), "r"(a2), "r"(a3), "r"(blo), "r"(bhi), "n"(TB), "r"(sd)); }
};
template<> struct WG<224> { template<int TA, int TB> static __device__ __forceinline__ void ss(float* d, uint32_t alo, uint32_t ahi, uint32_t blo, uint32_t bhi, int sd) {
  asm volatile("{ .reg .pred p; .reg .b64 da, db; mov.b64 da, {%112,%113}; mov.b64 db, {%114,%115}; setp.ne.b32 p, %116, 0;\n"
    "wgmma.mma_async.sync.aligned.m64n224k16.f32.bf16.bf16 {%0,%1,%2,%3,%4,%5,%6,%7,%8,%9,%10,%11,%12,%13,%14,%15,%16,%17,%18,%19,%20,%21,%22,%23,%24,%25,%26,%27,%28,%29,%30,%31,%32,%33,%34,%35,%36,%37,%38,%39,%40,%41,%42,%43,%44,%45,%46,%47,%48,%49,%50,%51,%52,%53,%54,%55,%56,%57,%58,%59,%60,%61,%62,%63,%64,%65,%66,%67,%68,%69,%70,%71,%72,%73,%74,%75,%76,%77,%78,%79,%80,%81,%82,%83,%84,%85,%86,%87,%88,%89,%90,%91,%92,%93,%94,%95,%96,%97,%98,%99,%100,%101,%102,%103,%104,%105,%106,%107,%108,%109,%110,%111}, da, db, p, 1, 1, %117, %118; }"
    : "+f"(d[0]),"+f"(d[1]),"+f"(d[2]),"+f"(d[3]),"+f"(d[4]),"+f"(d[5]),"+f"(d[6]),"+f"(d[7]),"+f"(d[8]),"+f"(d[9]),"+f"(d[10]),"+f"(d[11]),"+f"(d[12]),"+f"(d[13]),"+f"(d[14]),"+f"(d[15]),"+f"(d[16]),"+f"(d[17]),"+f"(d[18]),"+f"(d[19]),"+f"(d[20]),"+f"(d[21]),"+f"(d[22]),"+f"(d[23]),"+f"(d[24]),"+f"(d[25]),"+f"(d[26]),"+f"(d[27]),"+f"(d[28]),"+f"(d[29]),"+f"(d[30]),"+f"(d[31]),"+f"(d[32]),"+f"(d[33]),"+f"(d[34]),"+f"(d[35]),"+f"(d[36]),"+f"(d[37]),"+f"(d[38]),"+f"(d[39]),"+f"(d[40]),"+f"(d[41]),"+f"(d[42]),"+f"(d[43]),"+f"(d[44]),"+f"(d[45]),"+f"(d[46]),"+f"(d[47]),"+f"(d[48]),"+f"(d[49]),"+f"(d[50]),"+f"(d[51]),"+f"(d[52]),"+f"(d[53]),"+f"(d[54]),"+f"(d[55]),"+f"(d[56]),"+f"(d[57]),"+f"(d[58]),"+f"(d[59]),"+f"(d[60]),"+f"(d[61]),"+f"(d[62]),"+f"(d[63]),"+f"(d[64]),"+f"(d[65]),"+f"(d[66]),"+f"(d[67]),"+f"(d[68]),"+f"(d[69]),"+f"(d[70]),"+f"(d[71]),"+f"(d[72]),"+f"(d[73]),"+f"(d[74]),"+f"(d[75]),"+f"(d[76]),"+f"(d[77]),"+f"(d[78]),"+f"(d[79]),"+f"(d[80]),"+f"(d[81]),"+f"(d[82]),"+f"(d[83]),"+f"(d[84]),"+f"(d[85]),"+f"(d[86]),"+f"(d[87]),"+f"(d[88]),"+f"(d[89]),"+f"(d[90]),"+f"(d[91]),"+f"(d[92]),"+f"(d[93]),"+f"(d[94]),"+f"(d[95]),"+f"(d[96]),"+f"(d[97]),"+f"(d[98]),"+f"(d[99]),"+f"(d[100]),"+f"(d[101]),"+f"(d[102]),"+f"(d[103]),"+f"(d[104]),"+f"(d[105]),"+f"(d[106]),"+f"(d[107]),"+f"(d[108]),"+f"(d[109]),"+f"(d[110]),"+f"(d[111])
    : "r"(alo), "r"(ahi), "r"(blo), "r"(bhi), "r"(sd), "n"(TA), "n"(TB)); }
  template<int TB> static __device__ __forceinline__ void rs(float* d, uint32_t a0, uint32_t a1, uint32_t a2, uint32_t a3, uint32_t blo, uint32_t bhi, int sd) {
  asm volatile("{ .reg .pred p; .reg .b64 db; mov.b64 db, {%116,%117}; setp.ne.b32 p, %119, 0;\n"
    "wgmma.mma_async.sync.aligned.m64n224k16.f32.bf16.bf16 {%0,%1,%2,%3,%4,%5,%6,%7,%8,%9,%10,%11,%12,%13,%14,%15,%16,%17,%18,%19,%20,%21,%22,%23,%24,%25,%26,%27,%28,%29,%30,%31,%32,%33,%34,%35,%36,%37,%38,%39,%40,%41,%42,%43,%44,%45,%46,%47,%48,%49,%50,%51,%52,%53,%54,%55,%56,%57,%58,%59,%60,%61,%62,%63,%64,%65,%66,%67,%68,%69,%70,%71,%72,%73,%74,%75,%76,%77,%78,%79,%80,%81,%82,%83,%84,%85,%86,%87,%88,%89,%90,%91,%92,%93,%94,%95,%96,%97,%98,%99,%100,%101,%102,%103,%104,%105,%106,%107,%108,%109,%110,%111}, {%112,%113,%114,%115}, db, p, 1, 1, %118; }"
    : "+f"(d[0]),"+f"(d[1]),"+f"(d[2]),"+f"(d[3]),"+f"(d[4]),"+f"(d[5]),"+f"(d[6]),"+f"(d[7]),"+f"(d[8]),"+f"(d[9]),"+f"(d[10]),"+f"(d[11]),"+f"(d[12]),"+f"(d[13]),"+f"(d[14]),"+f"(d[15]),"+f"(d[16]),"+f"(d[17]),"+f"(d[18]),"+f"(d[19]),"+f"(d[20]),"+f"(d[21]),"+f"(d[22]),"+f"(d[23]),"+f"(d[24]),"+f"(d[25]),"+f"(d[26]),"+f"(d[27]),"+f"(d[28]),"+f"(d[29]),"+f"(d[30]),"+f"(d[31]),"+f"(d[32]),"+f"(d[33]),"+f"(d[34]),"+f"(d[35]),"+f"(d[36]),"+f"(d[37]),"+f"(d[38]),"+f"(d[39]),"+f"(d[40]),"+f"(d[41]),"+f"(d[42]),"+f"(d[43]),"+f"(d[44]),"+f"(d[45]),"+f"(d[46]),"+f"(d[47]),"+f"(d[48]),"+f"(d[49]),"+f"(d[50]),"+f"(d[51]),"+f"(d[52]),"+f"(d[53]),"+f"(d[54]),"+f"(d[55]),"+f"(d[56]),"+f"(d[57]),"+f"(d[58]),"+f"(d[59]),"+f"(d[60]),"+f"(d[61]),"+f"(d[62]),"+f"(d[63]),"+f"(d[64]),"+f"(d[65]),"+f"(d[66]),"+f"(d[67]),"+f"(d[68]),"+f"(d[69]),"+f"(d[70]),"+f"(d[71]),"+f"(d[72]),"+f"(d[73]),"+f"(d[74]),"+f"(d[75]),"+f"(d[76]),"+f"(d[77]),"+f"(d[78]),"+f"(d[79]),"+f"(d[80]),"+f"(d[81]),"+f"(d[82]),"+f"(d[83]),"+f"(d[84]),"+f"(d[85]),"+f"(d[86]),"+f"(d[87]),"+f"(d[88]),"+f"(d[89]),"+f"(d[90]),"+f"(d[91]),"+f"(d[92]),"+f"(d[93]),"+f"(d[94]),"+f"(d[95]),"+f"(d[96]),"+f"(d[97]),"+f"(d[98]),"+f"(d[99]),"+f"(d[100]),"+f"(d[101]),"+f"(d[102]),"+f"(d[103]),"+f"(d[104]),"+f"(d[105]),"+f"(d[106]),"+f"(d[107]),"+f"(d[108]),"+f"(d[109]),"+f"(d[110]),"+f"(d[111])
    : "r"(a0), "r"(a1), "r"(a2), "r"(a3), "r"(blo), "r"(bhi), "n"(TB), "r"(sd)); }
};
template<> struct WG<240> { template<int TA, int TB> static __device__ __forceinline__ void ss(float* d, uint32_t alo, uint32_t ahi, uint32_t blo, uint32_t bhi, int sd) {
  asm volatile("{ .reg .pred p; .reg .b64 da, db; mov.b64 da, {%120,%121}; mov.b64 db, {%122,%123}; setp.ne.b32 p, %124, 0;\n"
    "wgmma.mma_async.sync.aligned.m64n240k16.f32.bf16.bf16 {%0,%1,%2,%3,%4,%5,%6,%7,%8,%9,%10,%11,%12,%13,%14,%15,%16,%17,%18,%19,%20,%21,%22,%23,%24,%25,%26,%27,%28,%29,%30,%31,%32,%33,%34,%35,%36,%37,%38,%39,%40,%41,%42,%43,%44,%45,%46,%47,%48,%49,%50,%51,%52,%53,%54,%55,%56,%57,%58,%59,%60,%61,%62,%63,%64,%65,%66,%67,%68,%69,%70,%71,%72,%73,%74,%75,%76,%77,%78,%79,%80,%81,%82,%83,%84,%85,%86,%87,%88,%89,%90,%91,%92,%93,%94,%95,%96,%97,%98,%99,%100,%101,%102,%103,%104,%105,%106,%107,%108,%109,%110,%111,%112,%113,%114,%115,%116,%117,%118,%119}, da, db, p, 1, 1, %125, %126; }"
    : "+f"(d[0]),"+f"(d[1]),"+f"(d[2]),"+f"(d[3]),"+f"(d[4]),"+f"(d[5]),"+f"(d[6]),"+f"(d[7]),"+f"(d[8]),"+f"(d[9]),"+f"(d[10]),"+f"(d[11]),"+f"(d[12]),"+f"(d[13]),"+f"(d[14]),"+f"(d[15]),"+f"(d[16]),"+f"(d[17]),"+f"(d[18]),"+f"(d[19]),"+f"(d[20]),"+f"(d[21]),"+f"(d[22]),"+f"(d[23]),"+f"(d[24]),"+f"(d[25]),"+f"(d[26]),"+f"(d[27]),"+f"(d[28]),"+f"(d[29]),"+f"(d[30]),"+f"(d[31]),"+f"(d[32]),"+f"(d[33]),"+f"(d[34]),"+f"(d[35]),"+f"(d[36]),"+f"(d[37]),"+f"(d[38]),"+f"(d[39]),"+f"(d[40]),"+f"(d[41]),"+f"(d[42]),"+f"(d[43]),"+f"(d[44]),"+f"(d[45]),"+f"(d[46]),"+f"(d[47]),"+f"(d[48]),"+f"(d[49]),"+f"(d[50]),"+f"(d[51]),"+f"(d[52]),"+f"(d[53]),"+f"(d[54]),"+f"(d[55]),"+f"(d[56]),"+f"(d[57]),"+f"(d[58]),"+f"(d[59]),"+f"(d[60]),"+f"(d[61]),"+f"(d[62]),"+f"(d[63]),"+f"(d[64]),"+f"(d[65]),"+f"(d[66]),"+f"(d[67]),"+f"(d[68]),"+f"(d[69]),"+f"(d[70]),"+f"(d[71]),"+f"(d[72]),"+f"(d[73]),"+f"(d[74]),"+f"(d[75]),"+f"(d[76]),"+f"(d[77]),"+f"(d[78]),"+f"(d[79]),"+f"(d[80]),"+f"(d[81]),"+f"(d[82]),"+f"(d[83]),"+f"(d[84]),"+f"(d[85]),"+f"(d[86]),"+f"(d[87]),"+f"(d[88]),"+f"(d[89]),"+f"(d[90]),"+f"(d[91]),"+f"(d[92]),"+f"(d[93]),"+f"(d[94]),"+f"(d[95]),"+f"(d[96]),"+f"(d[97]),"+f"(d[98]),"+f"(d[99]),"+f"(d[100]),"+f"(d[101]),"+f"(d[102]),"+f"(d[103]),"+f"(d[104]),"+f"(d[105]),"+f"(d[106]),"+f"(d[107]),"+f"(d[108]),"+f"(d[109]),"+f"(d[110]),"+f"(d[111]),"+f"(d[112]),"+f"(d[113]),"+f"(d[114]),"+f"(d[115]),"+f"(d[116]),"+f"(d[117]),"+f"(d[118]),"+f"(d[119])
    : "r"(alo), "r"(ahi), "r"(blo), "r"(bhi), "r"(sd), "n"(TA), "n"(TB)); }
  template<int TB> static __device__ __forceinline__ void rs(float* d, uint32_t a0, uint32_t a1, uint32_t a2, uint32_t a3, uint32_t blo, uint32_t bhi, int sd) {
  asm volatile("{ .reg .pred p; .reg .b64 db; mov.b64 db, {%124,%125}; setp.ne.b32 p, %127, 0;\n"
    "wgmma.mma_async.sync.aligned.m64n240k16.f32.bf16.bf16 {%0,%1,%2,%3,%4,%5,%6,%7,%8,%9,%10,%11,%12,%13,%14,%15,%16,%17,%18,%19,%20,%21,%22,%23,%24,%25,%26,%27,%28,%29,%30,%31,%32,%33,%34,%35,%36,%37,%38,%39,%40,%41,%42,%43,%44,%45,%46,%47,%48,%49,%50,%51,%52,%53,%54,%55,%56,%57,%58,%59,%60,%61,%62,%63,%64,%65,%66,%67,%68,%69,%70,%71,%72,%73,%74,%75,%76,%77,%78,%79,%80,%81,%82,%83,%84,%85,%86,%87,%88,%89,%90,%91,%92,%93,%94,%95,%96,%97,%98,%99,%100,%101,%102,%103,%104,%105,%106,%107,%108,%109,%110,%111,%112,%113,%114,%115,%116,%117,%118,%119}, {%120,%121,%122,%123}, db, p, 1, 1, %126; }"
    : "+f"(d[0]),"+f"(d[1]),"+f"(d[2]),"+f"(d[3]),"+f"(d[4]),"+f"(d[5]),"+f"(d[6]),"+f"(d[7]),"+f"(d[8]),"+f"(d[9]),"+f"(d[10]),"+f"(d[11]),"+f"(d[12]),"+f"(d[13]),"+f"(d[14]),"+f"(d[15]),"+f"(d[16]),"+f"(d[17]),"+f"(d[18]),"+f"(d[19]),"+f"(d[20]),"+f"(d[21]),"+f"(d[22]),"+f"(d[23]),"+f"(d[24]),"+f"(d[25]),"+f"(d[26]),"+f"(d[27]),"+f"(d[28]),"+f"(d[29]),"+f"(d[30]),"+f"(d[31]),"+f"(d[32]),"+f"(d[33]),"+f"(d[34]),"+f"(d[35]),"+f"(d[36]),"+f"(d[37]),"+f"(d[38]),"+f"(d[39]),"+f"(d[40]),"+f"(d[41]),"+f"(d[42]),"+f"(d[43]),"+f"(d[44]),"+f"(d[45]),"+f"(d[46]),"+f"(d[47]),"+f"(d[48]),"+f"(d[49]),"+f"(d[50]),"+f"(d[51]),"+f"(d[52]),"+f"(d[53]),"+f"(d[54]),"+f"(d[55]),"+f"(d[56]),"+f"(d[57]),"+f"(d[58]),"+f"(d[59]),"+f"(d[60]),"+f"(d[61]),"+f"(d[62]),"+f"(d[63]),"+f"(d[64]),"+f"(d[65]),"+f"(d[66]),"+f"(d[67]),"+f"(d[68]),"+f"(d[69]),"+f"(d[70]),"+f"(d[71]),"+f"(d[72]),"+f"(d[73]),"+f"(d[74]),"+f"(d[75]),"+f"(d[76]),"+f"(d[77]),"+f"(d[78]),"+f"(d[79]),"+f"(d[80]),"+f"(d[81]),"+f"(d[82]),"+f"(d[83]),"+f"(d[84]),"+f"(d[85]),"+f"(d[86]),"+f"(d[87]),"+f"(d[88]),"+f"(d[89]),"+f"(d[90]),"+f"(d[91]),"+f"(d[92]),"+f"(d[93]),"+f"(d[94]),"+f"(d[95]),"+f"(d[96]),"+f"(d[97]),"+f"(d[98]),"+f"(d[99]),"+f"(d[100]),"+f"(d[101]),"+f"(d[102]),"+f"(d[103]),"+f"(d[104]),"+f"(d[105]),"+f"(d[106]),"+f"(d[107]),"+f"(d[108]),"+f"(d[109]),"+f"(d[110]),"+f"(d[111]),"+f"(d[112]),"+f"(d[113]),"+f"(d[114]),"+f"(d[115]),"+f"(d[116]),"+f"(d[117]),"+f"(d[118]),"+f"(d[119])
    : "r"(a0), "r"(a1), "r"(a2), "r"(a3), "r"(blo), "r"(bhi), "n"(TB), "r"(sd)); }
};
template<> struct WG<256> { template<int TA, int TB> static __device__ __forceinline__ void ss(float* d, uint32_t alo, uint32_t ahi, uint32_t blo, uint32_t bhi, int sd) {
  asm volatile("{ .reg .pred p; .reg .b64 da, db; mov.b64 da, {%128,%129}; mov.b64 db, {%130,%131}; setp.ne.b32 p, %132, 0;\n"
    "wgmma.mma_async.sync.aligned.m64n256k16.f32.bf16.bf16 {%0,%1,%2,%3,%4,%5,%6,%7,%8,%9,%10,%11,%12,%13,%14,%15,%16,%17,%18,%19,%20,%21,%22,%23,%24,%25,%26,%27,%28,%29,%30,%31,%32,%33,%34,%35,%36,%37,%38,%39,%40,%41,%42,%43,%44,%45,%46,%47,%48,%49,%50,%51,%52,%53,%54,%55,%56,%57,%58,%59,%60,%61,%62,%63,%64,%65,%66,%67,%68,%69,%70,%71,%72,%73,%74,%75,%76,%77,%78,%79,%80,%81,%82,%83,%84,%85,%86,%87,%88,%89,%90,%91,%92,%93,%94,%95,%96,%97,%98,%99,%100,%101,%102,%103,%104,%105,%106,%107,%108,%109,%110,%111,%112,%113,%114,%115,%116,%117,%118,%119,%120,%121,%122,%123,%124,%125,%126,%127}, da, db, p, 1, 1, %133, %134; }"
    : "+f"(d[0]),"+f"(d[1]),"+f"(d[2]),"+f"(d[3]),"+f"(d[4]),"+f"(d[5]),"+f"(d[6]),"+f"(d[7]),"+f"(d[8]),"+f"(d[9]),"+f"(d[10]),"+f"(d[11]),"+f"(d[12]),"+f"(d[13]),"+f"(d[14]),"+f"(d[15]),"+f"(d[16]),"+f"(d[17]),"+f"(d[18]),"+f"(d[19]),"+f"(d[20]),"+f"(d[21]),"+f"(d[22]),"+f"(d[23]),"+f"(d[24]),"+f"(d[25]),"+f"(d[26]),"+f"(d[27]),"+f"(d[28]),"+f"(d[29]),"+f"(d[30]),"+f"(d[31]),"+f"(d[32]),"+f"(d[33]),"+f"(d[34]),"+f"(d[35]),"+f"(d[36]),"+f"(d[37]),"+f"(d[38]),"+f"(d[39]),"+f"(d[40]),"+f"(d[41]),"+f"(d[42]),"+f"(d[43]),"+f"(d[44]),"+f"(d[45]),"+f"(d[46]),"+f"(d[47]),"+f"(d[48]),"+f"(d[49]),"+f"(d[50]),"+f"(d[51]),"+f"(d[52]),"+f"(d[53]),"+f"(d[54]),"+f"(d[55]),"+f"(d[56]),"+f"(d[57]),"+f"(d[58]),"+f"(d[59]),"+f"(d[60]),"+f"(d[61]),"+f"(d[62]),"+f"(d[63]),"+f"(d[64]),"+f"(d[65]),"+f"(d[66]),"+f"(d[67]),"+f"(d[68]),"+f"(d[69]),"+f"(d[70]),"+f"(d[71]),"+f"(d[72]),"+f"(d[73]),"+f"(d[74]),"+f"(d[75]),"+f"(d[76]),"+f"(d[77]),"+f"(d[78]),"+f"(d[79]),"+f"(d[80]),"+f"(d[81]),"+f"(d[82]),"+f"(d[83]),"+f"(d[84]),"+f"(d[85]),"+f"(d[86]),"+f"(d[87]),"+f"(d[88]),"+f"(d[89]),"+f"(d[90]),"+f"(d[91]),"+f"(d[92]),"+f"(d[93]),"+f"(d[94]),"+f"(d[95]),"+f"(d[96]),"+f"(d[97]),"+f"(d[98]),"+f"(d[99]),"+f"(d[100]),"+f"(d[101]),"+f"(d[102]),"+f"(d[103]),"+f"(d[104]),"+f"(d[105]),"+f"(d[106]),"+f"(d[107]),"+f"(d[108]),"+f"(d[109]),"+f"(d[110]),"+f"(d[111]),"+f"(d[112]),"+f"(d[113]),"+f"(d[114]),"+f"(d[115]),"+f"(d[116]),"+f"(d[117]),"+f"(d[118]),"+f"(d[119]),"+f"(d[120]),"+f"(d[121]),"+f"(d[122]),"+f"(d[123]),"+f"(d[124]),"+f"(d[125]),"+f"(d[126]),"+f"(d[127])
    : "r"(alo), "r"(ahi), "r"(blo), "r"(bhi), "r"(sd), "n"(TA), "n"(TB)); }
  template<int TB> static __device__ __forceinline__ void rs(float* d, uint32_t a0, uint32_t a1, uint32_t a2, uint32_t a3, uint32_t blo, uint32_t bhi, int sd) {
  asm volatile("{ .reg .pred p; .reg .b64 db; mov.b64 db, {%132,%133}; setp.ne.b32 p, %135, 0;\n"
    "wgmma.mma_async.sync.aligned.m64n256k16.f32.bf16.bf16 {%0,%1,%2,%3,%4,%5,%6,%7,%8,%9,%10,%11,%12,%13,%14,%15,%16,%17,%18,%19,%20,%21,%22,%23,%24,%25,%26,%27,%28,%29,%30,%31,%32,%33,%34,%35,%36,%37,%38,%39,%40,%41,%42,%43,%44,%45,%46,%47,%48,%49,%50,%51,%52,%53,%54,%55,%56,%57,%58,%59,%60,%61,%62,%63,%64,%65,%66,%67,%68,%69,%70,%71,%72,%73,%74,%75,%76,%77,%78,%79,%80,%81,%82,%83,%84,%85,%86,%87,%88,%89,%90,%91,%92,%93,%94,%95,%96,%97,%98,%99,%100,%101,%102,%103,%104,%105,%106,%107,%108,%109,%110,%111,%112,%113,%114,%115,%116,%117,%118,%119,%120,%121,%122,%123,%124,%125,%126,%127}, {%128,%129,%130,%131}, db, p, 1, 1, %134; }"
    : "+f"(d[0]),"+f"(d[1]),"+f"(d[2]),"+f"(d[3]),"+f"(d[4]),"+f"(d[5]),"+f"(d[6]),"+f"(d[7]),"+f"(d[8]),"+f"(d[9]),"+f"(d[10]),"+f"(d[11]),"+f"(d[12]),"+f"(d[13]),"+f"(d[14]),"+f"(d[15]),"+f"(d[16]),"+f"(d[17]),"+f"(d[18]),"+f"(d[19]),"+f"(d[20]),"+f"(d[21]),"+f"(d[22]),"+f"(d[23]),"+f"(d[24]),"+f"(d[25]),"+f"(d[26]),"+f"(d[27]),"+f"(d[28]),"+f"(d[29]),"+f"(d[30]),"+f"(d[31]),"+f"(d[32]),"+f"(d[33]),"+f"(d[34]),"+f"(d[35]),"+f"(d[36]),"+f"(d[37]),"+f"(d[38]),"+f"(d[39]),"+f"(d[40]),"+f"(d[41]),"+f"(d[42]),"+f"(d[43]),"+f"(d[44]),"+f"(d[45]),"+f"(d[46]),"+f"(d[47]),"+f"(d[48]),"+f"(d[49]),"+f"(d[50]),"+f"(d[51]),"+f"(d[52]),"+f"(d[53]),"+f"(d[54]),"+f"(d[55]),"+f"(d[56]),"+f"(d[57]),"+f"(d[58]),"+f"(d[59]),"+f"(d[60]),"+f"(d[61]),"+f"(d[62]),"+f"(d[63]),"+f"(d[64]),"+f"(d[65]),"+f"(d[66]),"+f"(d[67]),"+f"(d[68]),"+f"(d[69]),"+f"(d[70]),"+f"(d[71]),"+f"(d[72]),"+f"(d[73]),"+f"(d[74]),"+f"(d[75]),"+f"(d[76]),"+f"(d[77]),"+f"(d[78]),"+f"(d[79]),"+f"(d[80]),"+f"(d[81]),"+f"(d[82]),"+f"(d[83]),"+f"(d[84]),"+f"(d[85]),"+f"(d[86]),"+f"(d[87]),"+f"(d[88]),"+f"(d[89]),"+f"(d[90]),"+f"(d[91]),"+f"(d[92]),"+f"(d[93]),"+f"(d[94]),"+f"(d[95]),"+f"(d[96]),"+f"(d[97]),"+f"(d[98]),"+f"(d[99]),"+f"(d[100]),"+f"(d[101]),"+f"(d[102]),"+f"(d[103]),"+f"(d[104]),"+f"(d[105]),"+f"(d[106]),"+f"(d[107]),"+f"(d[108]),"+f"(d[109]),"+f"(d[110]),"+f"(d[111]),"+f"(d[112]),"+f"(d[113]),"+f"(d[114]),"+f"(d[115]),"+f"(d[116]),"+f"(d[117]),"+f"(d[118]),"+f"(d[119]),"+f"(d[120]),"+f"(d[121]),"+f"(d[122]),"+f"(d[123]),"+f"(d[124]),"+f"(d[125]),"+f"(d[126]),"+f"(d[127])
    : "r"(a0), "r"(a1), "r"(a2), "r"(a3), "r"(blo), "r"(bhi), "n"(TB), "r"(sd)); }
};

template<int T> struct ConvR {
    static __device__ __forceinline__ void run(float* acc, const uint32_t* a, uint32_t db) {
        WG<256 - 16 * T>::template rs<0>(acc, a[4 * T], a[4 * T + 1], a[4 * T + 2], a[4 * T + 3], db + T * 16, dhi(128, 0), T != 0);
        ConvR<T + 1>::run(acc, a, db);
    }
};
template<> struct ConvR<16> { static __device__ __forceinline__ void run(float*, const uint32_t*, uint32_t) {} };

template<int O2> __device__ __forceinline__ bool check_tile(uint32_t a, uint32_t tag) {
    uint32_t bad;
    asm("{ .reg .b32 x, y; lop3.b32 x, %1, %2, %5, 0x7e; lop3.b32 y, %3, %4, %5, 0x7e; lop3.b32 %0, x, y, 1, 0xa8; }" : "=r"(bad) : "r"(lds32(a)), "r"(lds32(a + 128)), "r"(lds32(a + O2)), "r"(lds32(a + O2 + 128)), "r"(tag));
    return __any_sync(~0u, bad);
}
template<int N, int O1, int O2> __device__ __forceinline__ void repair_tile(uint32_t a, const char* g, uint32_t tag) {
    asm volatile("{\n .reg .pred p, q; .reg .b32 i, n, u, t, x, y, z, w; .reg .b64 ga, lo, hi; .reg .b128 v; mov.u32 i, 0; mov.u32 n, 0;\n"
                 "LAB_RP:\n and.b32 t, i, 1; mul.lo.u32 u, t, %4; shr.u32 t, i, 1; mad.lo.u32 u, t, %3, u; add.u32 t, u, %0; and.b32 u, t, 0xfffffff0; cvt.u64.u32 ga, u; add.u64 ga, ga, %1;\n"
                 " ld.relaxed.gpu.global.b128 v, [ga]; mov.b128 {lo, hi}, v; mov.b64 {x, y}, lo; mov.b64 {z, w}, hi; st.shared.v4.b32 [u], {x, y, z, w}; ld.volatile.shared.b32 t, [t];\n"
                 " xor.b32 t, t, %2; and.b32 t, t, 1; setp.ne.u32 p, t, 0; vote.sync.any.pred p, p, 0xffffffff; add.u32 n, n, 1; setp.lt.and.u32 p, n, 20000, p; @!p add.u32 i, i, 1;\n"
                 " setp.lt.u32 q, i, %5;\n @q bra.uni LAB_RP;\n fence.proxy.async.shared::cta;\n }" :: "r"(a), "l"(g), "r"(tag), "n"(O2), "n"(O1), "n"(N) : "memory");
    __syncwarp();
}
template<int P> __device__ __forceinline__ void hh_store(const uint32_t* hq, char* dst) { const uint32_t* o = hq + 4 * P; stg_v4(dst + (P >> 2) * 16384 + ((P >> 1) & 1) * 512 + (P & 1) * 1024, o[0], o[1], o[2], o[3]); }
template<int P, bool ST = true> __device__ __forceinline__ void ffn_epi(const float* g, const float* u, float rq0, float rq1, uint32_t* hq, char* dst, uint32_t tag) {
    const float rq = (P & 1) ? rq1 : rq0;
    uint32_t* o = hq + 4 * P;
    #pragma unroll
    for (int b = 0; b < 4; b++) { const int i = 16 * (P >> 1) + 4 * b + 2 * (P & 1); o[b] = hmul2(pack2relu(g[i], g[i + 1]), pack2(u[i] * rq, u[i + 1] * rq)); }
    o[2 * (P & 1) + ((P >> 1) & 1)] = tagbit(o[2 * (P & 1) + ((P >> 1) & 1)], tag);
    if (ST) hh_store<P>(hq, dst); else asm volatile("" : "+r"(o[0]), "+r"(o[1]), "+r"(o[2]), "+r"(o[3]));
}
__device__ __forceinline__ uint32_t tagged(float x, uint32_t tag) { return (__float_as_uint(x) & ~7u) | (tag & 7u); }
__device__ __forceinline__ uint32_t split2(float x) { const float h = bfround(x); return pack2(h, x - h); }
__device__ __forceinline__ void yield() { asm volatile("pmevent 1;" ::: "memory"); }
__device__ __forceinline__ void vfma(float& d, float a, float b) { asm volatile("fma.rn.f32 %0, %1, %2, %0;" : "+f"(d) : "f"(a), "f"(b)); }
__device__ __forceinline__ void vadd(float& d, float a) { asm volatile("add.f32 %0, %0, %1;" : "+f"(d) : "f"(a)); }
template<int I, int N, typename F> __device__ __forceinline__ void static_for(F&& f) {
    if constexpr (I < N) { f(std::integral_constant<int, I>{}); static_for<I + 1, N>(f); }
}

__device__ __forceinline__ int mod_col(int G) {
    if (G >= 32 && G < 50) G = G < 34 ? G + 6 : G < 44 ? G + 6 : G - 12;
    const int s4 = (G >> 1) & 3;
    return G < 40 ? (s4 + (s4 == 3)) * 640 + (G >> 3) * 128 + (G & 1) * 64 : G * 64 - 640 * (G < 50);
}
__device__ __forceinline__ uint32_t silu2(uint32_t w) {
    const float a0 = bflo(w), a1 = bfhi(w);
    return pack2(__fdividef(a0, 1.f + __expf(-a0)), __fdividef(a1, 1.f + __expf(-a1)));
}

struct Maps { CUtensorMap k, v, q, o1, w[4]  , wd, wn, wm, out, ou2; };
struct Ptrs { char* scr; const char *k, *v, *shift, *ssmD, *ssm, *c, *Wg, *Wu, *Wd;
    uint32_t wl[8], zero[8];
};

__global__ void __cluster_dims__(2, 1, 1) __launch_bounds__(384, 1)
fused_kernel(const __grid_constant__ Ptrs P, const __grid_constant__ Maps M) {
    extern __shared__ __align__(1024) char smraw[];
    uint32_t clk0;
    asm volatile("mov.u32 %0, %%clock;" : "=r"(clk0));
    const uint32_t sb = smem_u32(smraw);
    const int tid = threadIdx.x, lane = tid & 31;
    uint32_t tpc;
    asm("mov.u32 %0, %%smid;" : "=r"(tpc));
    tpc >>= 1;
    const int b = 2 * (tpc >= 62 ? tpc - 62 : tpc + 4) + (blockIdx.x & 1);
    const int warp = __shfl_sync(~0u, tid >> 5, 0);
    #define BAR(i) (sb + BARS + 8 * (i))
    #define CNT(i) ((uint32_t*)paddv(P.scr, (i) * 128))
    uint32_t epoch = 0;
    if (tid == 288) { pf_map(&M.k); pf_map(&M.v); }
    const uint32_t pfo = ((blockIdx.x & 127) * 16 + (lane >> 1)) * 1280 + (lane & 1) * 128;
    if (warp == 0) asm volatile("prefetch.global.L2 [%0]; prefetch.global.L2 [%1];" :: "l"(padd(P.k, pfo)), "l"(padd(P.v, pfo)) : "memory");
    const int rank = b & 1, cl = b >> 1, cu = cl - 36, cv = (cu * 37) >> 8;
    const int gpc = cl < 4 ? 0 : cl < 36 ? (cl - 4) & 7 : 1 + cu - 7 * cv, pj = cl < 4 ? 4 + cl : cl < 36 ? (cl - 4) >> 3 : 4 + cv;
    const int sg = (0x73125460 >> (4 * gpc)) & 7;
    const int cg = 2 * (sg >> 2) + rank, tb = 8 * (sg & 3) + pj, bc = 32 * cg + tb;
    const int js = pj, tile = 2 * gpc + rank;
    const int kh = js >> 2, dq = js & 3;
    auto load_kv = [&](int r) {
        bulk_g2s(sb + SHT + r * 256, padd(P.shift, r * 1024 + cg * 256), 256, BAR(B_KV + r));
        tma3d(sb + kv_at(r), &M.k, r * 128 + cg * 32, 247 - 8 * tb, 0, BAR(B_KV + r));
        tma3d(sb + kv_at(r) + 4608, &M.v, r * 128 + cg * 32, 248 - 8 * tb, 0, BAR(B_KV + r));
    };
    auto load_h = [&](int r) { bulk_g2s(sb + 16 + h_at(r), padd(P.ssm, (bc + 128 * r) * 4096), 4096, BAR(B_H + r)); bulk_g2s(sb + DS + r * 16, padd(P.ssmD, (bc & ~7) * 2 + r * 256), 16, BAR(B_H + r)); };
    auto t_task = [&](int n, int t7, uint32_t tag, bool dry) {
        const int blk = t7 & 7, ch = 128 * n + 32 * cg + 2 * (t7 >> 3);
        uint32_t ka[8], sa = sb + SHT + n * 256 + (t7 >> 3) * 16;
        #pragma unroll
        for (int i = 0; i < 4; i++) { ka[i] = (sb + kv_at(n) + blk * 64 + (t7 >> 3) * 4) ^ ((blk * 8 + i * 8) & 0x30); ka[i + 4] = ka[i] ^ 0x20; }
        char* dst = SC(kvT, ch * 4096 + (8 * tb + 7 - blk) * 16);
        #pragma unroll
        for (int i = 0; i < 8; i++) asm volatile("" : "+r"(ka[i]));
        asm volatile("" : "+r"(sa), "+l"(dst));
        KSTAMP(t7 < 32 && n == 0, 190);
        mbar_wait(BAR(dry ? NBARS : B_KV + n), dry);
        KSTAMP(t7 < 32, 195 + n);
        const uint4 sw = lds128(sa);
        uint32_t kr[11], o[8];
        #pragma unroll
        for (int i = 0; i < 11; i++) { const int row = i < 3 ? 9 * (i + 5) : 9 * (i - 3) + 1; kr[i] = lds32(ka[row & 7] + row * 64); }
        #pragma unroll
        for (int i = 0; i < 8; i++) o[i] = lds32(ka[0] + 4608 + i * 512);
        const uint32_t w0 = prmt(sw.x, sw.z, 0x5410), w1 = prmt(sw.x, sw.z, 0x7632), w2 = prmt(sw.y, sw.w, 0x5410), w3 = prmt(sw.y, sw.w, 0x7632);
        #pragma unroll
        for (int i = 0; i < 8; i++) o[i] = hmul2(o[i], hfma2(kr[i + 3], w0, hfma2(kr[i + 2], w1, hfma2(kr[i + 1], w2, hmul2(kr[i], w3)))));
        if (!dry) stg_tag2<4096>(dst, prmt(o[7], o[6], 0x5410), prmt(o[5], o[4], 0x5410), prmt(o[3], o[2], 0x5410), prmt(o[1], o[0], 0x5410),
                       prmt(o[7], o[6], 0x7632), prmt(o[5], o[4], 0x7632), prmt(o[3], o[2], 0x7632), prmt(o[1], o[0], 0x7632), tag);
    };
    if (warp == 9 && b < 128 && elect()) {
        mbar_init(BAR(B_KV), 1);
        fence_async_smem();
        mbar_expect(BAR(B_KV), KVP + 256);
        load_kv(0);
        KSTAMP(true, 183);
    }
    if (b >= 128) {
        if (warp < 8) asm volatile("ld.relaxed.gpu.global.u32 %0, [%1];" : "=r"(epoch) : "l"(CNT(C_ZO)) : "memory");
        if (tid == 256) { _Pragma("unroll") for (int i = 0; i < 16; i++) mbar_init(BAR(i), i < 8 ? 1 : 4); fence_async_smem(); }
        __syncthreads();
        if (warp >= 8) {
            if (elect()) {
                pf_map(&M.wm);
                wait_clock(clk0, SCH(d_sp) + (warp - 8) * SCH(g_sp));
                _Pragma("unroll 1") for (int i = 0; i < 15; i++) {
                    const int col = mod_col(4 * i + b - 128), s = (i & 1) * 4 + warp - 8;
                    mbar_wait(BAR(8 + s), ~(i >> 1) & 1);
                    mbar_expect(BAR(s), 20480);
                    tma2d(sb + s * 20480, &M.wm, col, (warp - 8) * 160, BAR(s));
                    if (i == 0) pause(4 * SCH(g_sp));
                }
            }
        } else {
            const int wg = warp >> 2;
            sts32(sb + 204800 + tid * 4, silu2(__ldg((const uint32_t*)P.c + tid)));
            if (tid < 64) sts32(sb + 205824 + tid * 4, silu2(__ldg((const uint32_t*)P.c + 256 + tid)));
            fence_async_smem();
            bar_sync(1, 256);
            epoch = (epoch >> 7) + 1;
            _Pragma("unroll 1") for (int i = wg; i < 15; i += 2) {
                float acc[8];
                char* mp = SC(mod, (mod_col(4 * i + b - 128) + (warp & 3) * 16 + (lane >> 2)) * 4);
                _Pragma("unroll 1") for (int j = 0; j < 4; j++) {
                    const int s = wg * 4 + j;
                    const uint32_t da = dlo(sb + s * 20480, 16), db = dlo(sb + 204800 + j * 320, 16);
                    mbar_wait(BAR(s), (i >> 1) & 1);
                    wg_fence();
                    #pragma unroll
                    for (int ks = 0; ks < 10; ks++) WG<8>::ss<1, 0>(acc + 4 * (ks & 1), da + ks * 128, dhi(1024, 1), db + ks * 2, dhi(128, 0), ks > 1 || j != 0);
                    wg_commit();
                    wg_wait<0>();
                    pin<8>(acc);
                    mbar_arrive_if(BAR(8 + s), lane == 0);
                }
                if ((lane & 3) == 0) asm volatile("st.relaxed.gpu.global.u32 [%0], %1; st.relaxed.gpu.global.u32 [%0+32], %2;" :: "l"(mp), "r"(tagged(acc[0] + acc[4], epoch)), "r"(tagged(acc[2] + acc[6], epoch)) : "memory");
                STAMPIF(warp == 4, 110 + (i >> 1));
                KSTAMP(warp == 0 && i == 12, 117);
            }
        }
        PROF_EXIT();
        return;
    }

    #define CLUSTER_ARRIVE() asm volatile("barrier.cluster.arrive.relaxed.aligned;" ::: "memory")
    if (warp < 8) {
        const int wg = warp >> 2, w = warp & 3;
        const int q = lane & 3, rr = lane >> 2;
        const bool l0 = lane == 0;
        if ((PF2 & 1) && warp == 1) asm volatile("prefetch.global.L2 [%0];" :: "l"(padd(P.ssm, bc * 4096 + lane * 128)) : "memory");
        if ((PF2 & 2) && warp == 2) asm volatile("prefetch.global.L2 [%0+256]; prefetch.global.L2 [%1+256];" :: "l"(padd(P.k, pfo)), "l"(padd(P.v, pfo)) : "memory");
        CLUSTER_ARRIVE();
        asm volatile("setmaxnreg.inc.sync.aligned.u32 224;");
        #define ln (t7 & 31)
        auto reduce = [&](int r, int t7, uint32_t tg, auto&& first) {
            char* yp = SC(yB, ((r * 4 + (bc >> 5)) * 32 + (t7 >> 3)) * 4096 + (bc & 31) * 128 + (((t7 & 7) ^ ((bc & 1) << 2)) << 4));
            void* hp = CNT(C_Y + 4 * r + (bc >> 5) + 32 * (ln & 1));
            asm volatile("" : "+l"(yp));
            first();
            bar_sync(5 + wg, 128);
            uint4 p[2][4];
            #pragma unroll
            for (int h = 0; h < 2; h++)
            #pragma unroll
            for (int k = 0; k < 4; k++) p[h][k] = lds128(sb + PB - wg * 32768 + (t7 + 128 * h) * 16 + k * (PP + 32));
            uint32_t y[8];
            #pragma unroll
            for (int j = 0; j < 8; j++) y[j] = hadd2((&p[j >> 2][0].x)[j & 3], hadd2((&p[j >> 2][1].x)[j & 3], hadd2((&p[j >> 2][2].x)[j & 3], (&p[j >> 2][3].x)[j & 3])));
            stg_tag2<65536>(yp, y[0], y[1], y[2], y[3], y[4], y[5], y[6], y[7], tg);
            if (w) {
                bar_arrive(8 + wg, 128);
            } else {
                bar_sync(8 + wg, 128);
                LATE(hint_cnt(hp, ln < 2));
                pre_add(sb + PRE + 44 + r * 8 + (ln & 1) * 20, ln < 1 + (r >= 3));
                STAMP(10 + r * 3);
            }
        };
        {
        int t7 = __shfl_sync(~0u, tid & 127, lane);
        auto ff_arrive = [&](int i, bool p) {
            uint32_t a;
            asm("mapa.shared::cluster.u32 %0, %1, %2;" : "=r"(a) : "r"(BAR(B_FF + i)), "r"(rank ^ (t7 & 1)));
            mbar_arrive_remote_if(a, p && ln < 2);
        };
        uint32_t fa[64];
        auto odd_copy = [&](int n) {
            const uint32_t src = sb + 16 + h_at(n) + t7 * 16, dst = sb + 16 + (wg ? HO1 : HO0) + t7 * 16;
            uint32_t dr;
            mbar_wait(BAR(B_H + n), 0);
            asm volatile("ld.shared.u16 %0, [%1];" : "=r"(dr) : "r"(sb + DS + n * 16 + (bc & 7) * 2) : "memory");
            KSTAMP(w == 0, 140 + n);
            uint4 v = lds128(src); const uint4 u = lds128(src + 2048);
            const uint32_t pv = lds32(src - 4), pu = lds32(src + 2044);
            if (t7 == 0) { v.x = hadd2(v.x, dr); sts32(src, v.x); }
            sts128(dst, prmt(pv, v.x, 0x5432), prmt(v.x, v.y, 0x5432), prmt(v.y, v.z, 0x5432), prmt(v.z, v.w, 0x5432));
            sts128(dst + 2048, prmt(pu, u.x, 0x5432), prmt(u.x, u.y, 0x5432), prmt(u.y, u.z, 0x5432), prmt(u.z, u.w, 0x5432));
        };
        auto frags = [&](int n, auto I0, auto I1) {
            const uint32_t a = sb + 16 + ((ln & 4) ? (wg ? HO1 : HO0) : h_at(n)) + 32 * w + 4 * (ln & 3) - 4 * (ln >> 3);
            #pragma unroll
            for (int i = I0.value; i < I1.value; i++) fa[i] = lds32(a + (i >> 2) * 256 + (i & 1) * 128 + (i & 2) * 8);
        };
        using I0 = std::integral_constant<int, 0>; using IA = std::integral_constant<int, FA>; using I64 = std::integral_constant<int, 64>;
        uint32_t list = P.wl[wg];
        t7 |= list >> 31;
        asm volatile("" : "+r"(t7));
        KSTAMP(warp == 0, 186);
        bar_sync(0, 384);
        KSTAMP(warp == 0, 189);
        epoch = __shfl_sync(~0u, lds32(sb + HT + 4), 0);
        _Pragma("unroll 1") for (int r = wg; r < 5; r += 2) {
            _Pragma("unroll 1") for (; list; list >>= 4) {
                const int n = (list & 7) - 1;
                t7 |= list >> 31;
                if (n < 5) {
                    void* hp = CNT(C_KV + 4 * n + cg + 32 * (ln & 1));
                    EARLY(mbar_wait(BAR(B_CR), 0); hint_cnt(hp, t7 < 2 && !(list & 8)));
                    t_task(n, t7, epoch, list & 8);
                    if (list & 8) continue;
                    if (n < 2) mbar_wait(BAR(B_CR), 0);
                    if (w) bar_arrive(10 + n, 128);
                    else {
                        bar_sync(10 + n, 128);
                        LATE(hint_cnt(hp, ln < 2));
                        pre_add(sb + PRE + n * 8 + 4, ln == 0);
                        ff_arrive(n >= 3, true);
                        KSTAMP(true, n);
                    }
                } else {
                    odd_copy(wg);
                    bar_sync(5 + wg, 128);
                    frags(wg, I0{}, I64{});
                    KSTAMP(w == 0, 145 + r);
                }
            }
            float acc[128];
            const uint32_t xa = sb + x_at(r), pb = sb + PB - wg * 32768, nx = BAR(r == 4 ? B_GO : B_XF + 1 + r);
            uint32_t db = dlo(xa, 16);
            list = P.wl[r + 2];
            t7 |= list >> 31;
            const uint32_t tg = epoch;
            if (r == 4) ff_arrive(2, true); else pre_add(sb + PRE + 80, ln == 0 && r >= 2);
            asm volatile("" : "+r"(db));
            EARLY(hint_cnt(CNT(C_Y + 4 * r + (bc >> 5) + 32 * (ln & 1)), t7 < 2));
            mbar_wait(BAR(B_XF + r), 0);
            KSTAMP(w == 0, 8 + r * 3); GSTAMPIF(w == 0 && r == 0, 63);
            _Pragma("unroll 1") for (int tries = 0;; tries++) {
                wg_fence();
                ConvR<0>::run(acc, fa, db);
                wg_commit();
                mbar_arrive_if(nx, ln == 0 && !tries);
                uint32_t bad = (lds32(xa + t7 * 16) ^ tg) | (lds32(xa + t7 * 16 + 2048) ^ tg);
                if (r < 3 && !tries) odd_copy(r + 2);
                wg_wait<0>();
                pin<128>(acc);
                asm volatile("{ .reg .pred p; setp.ne.b32 p, %1, 0; barrier.red.or.pred.aligned p, %2, 128, p; selp.u32 %0, 1, 0, p; }" : "=r"(bad) : "r"(bad & 1), "r"(5 + wg) : "memory");
                if (!bad || tries) break;
                repair_tile<2, 2048, 0>(xa + t7 * 16, SC(kvT, (bc + 128 * r) * 4096) - xa, tg);
                bar_sync(5 + wg, 128);
                STAMP(121);
            }
            STAMPIF(w == 0, 9 + r * 3);
            t7 |= list >> 30;
            const uint32_t pw = pb + w * PP + ln * 16;
            #pragma unroll
            for (int g = 0; g < 8; g++) {
                uint32_t o[4];
                #pragma unroll
                for (int l = 0; l < 4; l++) { const int i = 4 * g + l;
                    o[l] = i < 31 ? pack2(acc[4 * i] + acc[4 * i + 6], acc[4 * i + 1] + acc[4 * i + 7]) : pack2(acc[4 * i], acc[4 * i + 1]); }
                asm volatile("stmatrix.sync.aligned.m8n8.x4.trans.shared.b16 [%0], {%1,%2,%3,%4};" :: "r"(pw + g * 512), "r"(o[0]), "r"(o[1]), "r"(o[2]), "r"(o[3]) : "memory");
            }
            if (RD4 && r == 4) break;
            reduce(r, t7, tg, [&]() { if (FA && r < 3) frags(r + 2, I0{}, IA{}); });
            if (r < 3) { frags(r + 2, IA{}, I64{}); STAMPIF(w == 0, 147 + r); }
        }
        #undef ln
        }
        float acc1[128];
        const uint32_t tag = epoch;
        uint32_t g2e;
        asm("mapa.shared::cluster.u32 %0, %1, %2;" : "=r"(g2e) : "r"(BAR(lane == 2 ? B_HE - 2 : B_G2E)), "r"(rank ^ (lane & 1)));
        const bool l01 = lane < 2;
        const uint32_t wre = g2e - 8 * (B_G2E - B_WE);
        uint32_t p1a = dlo(sb + wg * 8192, 2048), p1s = 0;
        uint32_t va = sb + (w >> 1) * 2048 + (lane >> 3) * 516 + (lane & 1) * 64 + (lane & 2) * 128 + ((((w << 1) ^ lane) & 2) + ((lane >> 2) & 1)) * 16;
        uint32_t tw[4];
        auto a_ready = [&](int kb) {
            mbar_wait(BAR(B_AF) + kb * 8, 0);
            #pragma unroll
            for (int i = 0; i < 4; i++) tw[i] = lds32(va + (i & 1) * 128 + (i >> 1) * 4096);
        };
        auto a_check = [&]() {
            uint32_t bad;
            asm("{ .reg .b32 x, y; lop3.b32 x, %1, %2, %5, 0x7e; lop3.b32 y, %3, %4, %5, 0x7e; lop3.b32 %0, x, y, 1, 0xa8; }" : "=r"(bad) : "r"(tw[0]), "r"(tw[1]), "r"(tw[2]), "r"(tw[3]), "r"(tag));
            if (__builtin_expect(__any_sync(~0u, bad), 0)) { repair_tile<4, 128, 4096>(va, SC(z, tile * 163840) - sb, tag); STAMP(118); }
            va += 16384;
        };
        if (wg) {
            mbar_wait(BAR(B_AF), 0);
            if (__builtin_expect(check_tile<4096>(va, tag) | check_tile<4096>(va + 8192, tag), 0)) repair_tile<8, 128, 4096>(va, SC(z, tile * 163840) - sb, tag);
            mbar_arrive_if(BAR(B_GO), l0);
        }
        va += 16384 + wg * 8192;
        mbar_wait(BAR(B_GO), 0);
        KSTAMP(w == 0, 24 + wg);
        GSTAMPIF(warp == 0, 107);
        auto pass1 = [&](int k0, int k1, auto&& mid) {
            _Pragma("unroll 1") for (int kb = k0; kb < k1; kb++) {
                const uint32_t so = p1s & 16, db = dlo(sb + WR, 4096) + so * 128;
                #pragma unroll
                for (int h = 0; h < 2; h++) {
                    mbar_wait(BAR(B_WF + h) + so, p1s >> 31);
                    STAMPIF(warp == PW, 64 + 2 * kb + h);
                    wg_fence();
                    WG<256>::ss<1, 1>(acc1, p1a + h * 256, dhi(512, 2), db + h * 1024, dhi(1024, 1), (h || k0) ? 1 : kb);
                    mid(h, kb);
                    WG<256>::ss<1, 1>(acc1, p1a + h * 256 + 64, dhi(512, 2), db + h * 1024 + 128, dhi(1024, 1), 1);
                    wg_commit();
                    wg_wait<1>();
                    mbar_arrive_remote_if(wre + (h ? so : (so ^ 16) + 8), l01 && (kb + h) > 0);
                    if (h && k0 < 9) a_check();
                }
                p1a += 1024; p1s = (p1s ^ 16) + (so << 27);
            }
        };
        uint32_t ax[4];
        float acc2[64];
        float rq0, rq1;
        uint32_t m0, m1, d0, d1, stale;
        auto next_a = [&](int h, int kb) { if (RD4 && h == ((RD4 - 1) & 1) && kb == ((RD4 - 1) >> 1) && !wg) reduce(4, tid, tag, []() {}); if (h) a_ready(kb + 1); };
        pass1(0, KB_UT, next_a);
        {
            float au[8];
            const uint32_t ua = dlo(sb + UST + wg * 16384, 16), ub = dlo(sb + CS_TAB, 32);
            mbar_wait(BAR(B_UF), 0);
            KSTAMP(warp == 0, 33);
            wg_fence();
            #pragma unroll
            for (int ks = 0; ks < 8; ks++) WG<8>::ss<1, 0>(au + 4 * (ks & 1), ua + ks * 128, dhi(1024, 1), ub + ks * 4, dhi(128, 0), ks > 1);
            wg_commit();
            pass1(KB_UT, KB_UT + 1, [&](int h, int kb) { if (h) {
            pin<8>(au);
            pre_add(sb + PRE + 104, l0);
            const int t3 = (tile * 11) >> 5, cn = 2 * (tile - 3 * t3) + wg;
            asm volatile("{ .reg .pred p; .reg .b64 x; setp.eq.b32 p, %5, 0; mov.b64 x, {%1, %2}; @p st.relaxed.gpu.global.b64 [%0], x; mov.b64 x, {%3, %4}; @p st.relaxed.gpu.global.b64 [%0+64], x; }"
                         :: "l"(SC(ut, (t3 * 3072 + (cn >= 3) * 1344 + js * 192 + cn * 64 + w * 16 + rr) * 8)), "r"(tagged(au[0] + au[4], tag)), "f"(au[1] + au[5]), "r"(tagged(au[2] + au[6], tag)), "f"(au[3] + au[7]), "r"(q | (tile == 15)) : "memory");
            mbar_arrive_if(BAR(B_UD), l0);
            STAMPIF(warp == 0, 60);
            a_ready(kb + 1);
            } });
        }
        unsigned long long sv[8] = {};
        const char* s2p = SC(st2, ((tile * 2 + wg) * 256 + 63 - 16 * (rr >> 1) - (rr & 1) - 4 * w) * 8);
        auto st_load = [&](bool p) {
            #pragma unroll
            for (int i = 0; i < 8; i++)
                asm volatile("{ .reg .pred p; setp.ne.b32 p, %2, 0; @p ld.relaxed.gpu.global.b64 %0, [%1]; }" : "+l"(sv[i]) : "l"(s2p + (i & 3) * 512 - (i >> 2) * 16), "r"((int)p) : "memory");
        };
        auto st_row = [&](const unsigned long long* u, float& rq, uint32_t& m, uint32_t& d) {
            float2 v[4];
            #pragma unroll
            for (int i = 0; i < 4; i++) v[i] = make_float2(__uint_as_float((uint32_t)u[i]), __uint_as_float(u[i] >> 32));
            stale |= (__float_as_uint(v[0].x) ^ tag) | (__float_as_uint(v[1].x) ^ tag) | (__float_as_uint(v[2].x) ^ tag) | (__float_as_uint(v[3].x) ^ tag);
            const float mu = ((v[0].x + v[1].x) + (v[2].x + v[3].x)) * (1.f / D_), ve = fmaxf(((v[0].y + v[1].y) + (v[2].y + v[3].y)) * (1.f / D_) - mu * mu, 0.f) + 1e-5f;
            asm("rsqrt.approx.ftz.f32 %0, %1;" : "=f"(rq) : "f"(ve));
            d = split2(ve * rq); m = split2(-mu); rq *= rq;
            asm volatile("" : "+r"(d), "+r"(m), "+f"(rq), "+r"(stale) :: "memory");
        };
        pass1(KB_UT + 1, 9, [&](int h, int kb) { if (h == 0) st_load(kb == 8); else a_ready(kb + 1); });
        stale = 0;
        pass1(9, 10, [&](int h, int) { if (h == 0) st_row(sv, rq0, m0, d0); else st_row(sv + 4, rq1, m1, d1); });
        _Pragma("unroll 1") for (int it = 0; it < 20000 && __any_sync(~0u, (stale & 7) != 0); it++) { stale = 0; st_load(true); st_row(sv, rq0, m0, d0); st_row(sv + 4, rq1, m1, d1); }
        {
            const uint32_t zm = q == 0 ? ~0u : q == 1 ? 0xffffu : 0u, sh = q ? 0x5454 : 0x5410, sl = sh + 0x2222;
            ax[0] = prmt(m0, d0, sh) & zm; ax[1] = prmt(m1, d1, sh) & zm; ax[2] = prmt(m0, d0, sl) & zm; ax[3] = prmt(m1, d1, sl) & zm;
            asm volatile("" : "+r"(ax[0]), "+r"(ax[1]), "+r"(ax[2]), "+r"(ax[3]) :: "memory");
        }
        {
            mbar_wait(BAR(B_T1), 0);
            wg_fence();
            WG<256>::rs<1>(acc1, ax[0], ax[1], ax[2], ax[3], dlo(sb + TAB1, 0), dhi(48, 0), 1);
            WG<128>::rs<1>(acc2, ax[0], ax[1], ax[2], ax[3], dlo(sb + TAB2, 0), dhi(48, 0), 0);
            wg_commit();
        }
        char* hdst = SC(hh, (tile * 24 + js * 3) * 16384 + wg * 8192 + w * 2048 + rr * 64 + ((q ^ (rr >> 1)) << 4));
        wg_wait<1>();
        mbar_arrive_remote_if(wre + 24, l01);
        KSTAMP(w == 0, 26 + wg);
        GSTAMPIF(warp == 0, 108);
        uint32_t hq[48];
        static_for<0, 10>([&](auto IT) {
            constexpr int it = IT.value;
            mbar_wait(BAR(w2_bar(it)), it < 4);
            STAMPIF(warp == 0, 84 + it);
            const uint32_t da = dlo(sb + it * 16384 + wg * 8192, 2048), db = dlo(sb + w2_at(it), 8192);
            wg_fence();
            static_for<0, 4>([&](auto KS) {
                constexpr int ks = KS.value;
                WG<128>::ss<1, 1>(acc2, da + (ks >> 1) * 256 + (ks & 1) * 64, dhi(512, 2), db + ks * 128, dhi(1024, 1), 1);
                if constexpr (ks == 0) {
                    wg_commit();
                    wg_wait<1>();
                    if (it == 0) pin<128>(acc1);
                    if ((it > 0 && it < 6) || it == 7) mbar_arrive_remote_if(wre + 8 * (it == 7 ? 1 : (it + 3) & 3), l01);
                    static_for<0, 6>([&](auto G) { if constexpr (((B2S >> (4 * G.value)) & 15) == it) mbar_arrive_remote_if(g2e + 8 * G.value, l01); });
                }
                static_for<0, 8>([&](auto PP_) {
                    constexpr int hs = (HPS >> (4 * PP_.value)) & 15;
                    if constexpr (PP_.value == 2 * it + ks && ks < 2) ffn_epi<7 - PP_.value, false>(acc1, acc1 + 64, rq0, rq1, hq, hdst, tag);
                    if constexpr (hs == 2 * it + ks && ks < 2) hh_store<7 - PP_.value>(hq, hdst);
                    if constexpr ((PP_.value & 3) == 3 && (hs >> 1) == it && ks == 3) { __syncwarp(); mbar_arrive_if(BAR(PP_.value == 3 ? B_HD : B_HD + 1), l0); }
                });
            });
            wg_commit();
        });
        KSTAMP(w == 0, 30 + wg);
        {
            float acc[80];
            auto release = [&](int n) { wg_commit(); wg_wait<1>(); mbar_arrive_remote_if(g2e + 8 * (n - 1), lane < 2 + (n > 2 && n < 6)); };
            auto own = [&](auto IT) {
                constexpr int it = IT.value, n = it == 2 ? 5 : it;
                mbar_wait(BAR(B_G2F + n), 0);
                STAMPIF(w == 0 && it == 0, 34 + wg);
                STAMPIF(w == 0 && wg == kh, 94 + n);
                const uint32_t db = dlo(sb + g2b_at(n), 2048);
                #pragma unroll
                for (int i = 0; i < 16; i++) asm volatile("" : "+r"(hq[16 * it + i]) :: "memory");
                wg_fence();
                #pragma unroll
                for (int ks = 0; ks < 4; ks++) {
                    const uint32_t* o = hq + 16 * it + 8 * (ks >> 1) + 2 * (ks & 1);
                    WG<160>::rs<1>(acc, o[0], o[4], o[1], o[5], db + (ks >> 1) * 640 + (ks & 1) * 64, dhi(512, 2), it != 0 || ks != 0);
                    if (it == 0 && ks == 1) {
                        wg_commit();
                        wg_wait<1>();
                        pin<64>(acc2);
                        mbar_arrive_if(BAR(B_S0), l0);
                        static_for<0, 6>([&](auto G) { if constexpr (((B2S >> (4 * G.value)) & 15) == 10) mbar_arrive_remote_if(g2e + 8 * G.value, l01); });
                        ffn_epi<0>(acc2, acc2 + 32, rq0, rq1, hq + 32, hdst + 32768, tag);
                        wg_fence();
                    }
                    if (it && ks == 0) release(n);
                    if (it == 1 && ks == 0) ffn_epi<2>(acc2, acc2 + 32, rq0, rq1, hq + 32, hdst + 32768, tag);
                    if (it == 1 && ks == 1) { ffn_epi<3>(acc2, acc2 + 32, rq0, rq1, hq + 32, hdst + 32768, tag); __syncwarp(); mbar_arrive_if(BAR(B_HD), l0); }
                }
                wg_commit();
                if (it == 0) ffn_epi<1>(acc2, acc2 + 32, rq0, rq1, hq + 32, hdst + 32768, tag);
            };
            auto block = [&](int it, auto&& mid) {
                const int g = it >= 6 ? it - 6 : it, ga = ((it >= 6 ? 0x325104 : 0x32500) >> (4 * g)) & 7;
                const uint32_t da = dlo(sb + G2A + ga * 16384 + wg * 8192, 16), db = dlo(sb + g2b_at(g), 2048);
                mbar_wait(BAR(B_G2F + g), it >= 6);
                STAMPIF(w == 0 && it == 12 - SG, 36 + (wg ^ kh));
                STAMPIF(w == 0 && wg == kh, 94 + it);
                wg_fence();
                #pragma unroll
                for (int ks = 0; ks < 4; ks++) {
                    WG<160>::ss<0, 1>(acc, da + (ks >> 1) * 32 + (ks & 1) * 2, dhi(1024, 2), db + (ks >> 1) * 640 + (ks & 1) * 64, dhi(512, 2), 1);
                    mid(ks);
                }
                wg_commit();
            };
            own(std::integral_constant<int, 0>{}); own(std::integral_constant<int, 1>{});
            _Pragma("unroll 1") for (int it = 2; it < 5; it++) block(it, [&](int ks) { if (ks == 0) release(it); });
            own(std::integral_constant<int, 2>{});
            #pragma unroll
            for (int it = 6; it < 12 - SG; it++) block(it, [&](int ks) { if (ks == 0 && it == 6) release(it); });
            uint32_t gw[20], oa[10];
            const uint32_t ost = sb + G2A + warp * 2048, odd = dq & 1;
            const int row = S_ - 128 * tile - 16 * warp - 16;
            auto prep = [&]() {
            mbar_wait(BAR(B_X1), 0);
            #pragma unroll
            for (int i = 0; i < 5; i++) { const uint4 g = lds128(sb + GBT + q * 80 + i * 16); gw[4 * i] = g.x; gw[4 * i + 1] = g.y; gw[4 * i + 2] = g.z; gw[4 * i + 3] = g.w; }
            #pragma unroll
            for (int i = 0; i < 20; i++) asm volatile("" : "+r"(gw[i]));
            const uint32_t orow = 15 - (lane & 15);
            #pragma unroll
            for (int i = 0; i < 10; i++) {
                const int j = i < 2 ? (odd ? 8 + i : i) : i - 2 * odd;
                oa[i] = j < 8 ? ost + (j >> 2) * 16384 + orow * 128 + (((2 * (j & 3) + (lane >> 4)) ^ (orow & 7)) << 4) : ost + 32768 + orow * 64 + (((2 * (j & 1) + (lane >> 4)) ^ ((orow >> 1) & 3)) << 4);
                asm volatile("" : "+r"(oa[i]));
            }
            };
            if (wg != kh) { prep(); bar_sync(7, 256); }
            #pragma unroll
            for (int it = 12 - SG; it < 12; it++) block(it, [&](int) {});
            if (wg == kh) { bar_arrive(7, 256); prep(); }
            wg_wait<0>();
            pin<80>(acc);
            KSTAMP(w == 0, 38 + (wg ^ kh));
            GSTAMPIF(w == 0 && wg == kh, 109);
            #pragma unroll
            for (int i = 0; i < 10; i++) {
                uint32_t o[4];
                #pragma unroll
                for (int j = 0; j < 4; j++) { const int n = 4 * i + j; o[j] = hmul2(pack2(acc[2 * n], acc[2 * n + 1]), gw[n >> 1]); }
                asm volatile("stmatrix.sync.aligned.m8n8.x4.shared.b16 [%0], {%1,%2,%3,%4};" :: "r"(oa[i]), "r"(o[0]), "r"(o[1]), "r"(o[2]), "r"(o[3]) : "memory");
                if (ESPLIT && i == 5) {
                    fence_async_smem();
                    __syncwarp();
                    if (elect()) tma2d_red(&M.out, ost, dq * 160 + 32 * odd, row);
                }
            }
            fence_async_smem();
            __syncwarp();
            STAMPIF(w == 0, 123 + (wg ^ kh));
            if (elect()) {
                if (!ESPLIT) tma2d_red(&M.out, ost, dq * 160 + 32 * odd, row);
                tma2d_red(&M.out, ost + 16384, dq * 160 + 32 * odd + 64, row);
                tma2d_red(&M.ou2, ost + 32768, dq * 160 + 128 - 128 * odd, row);
                asm volatile("cp.async.bulk.commit_group;\n cp.async.bulk.wait_group.read 0;" ::: "memory");
            }
            KSTAMP(w == 0, 42 + (wg ^ kh));
            GSTAMPIF(w == 0 && wg == kh, 47);
        }
        PROF_EXIT();
    } else {
        asm volatile("setmaxnreg.dec.sync.aligned.u32 56;");
        if (warp == 9) {
        {
        if (elect()) {
            #pragma unroll
            for (int i = 1; i < B_XF; i++) mbar_init(BAR(i), 1);
            mbar_init(BAR(B_CR), 1); mbar_init(BAR(NBARS), 1);
            fence_async_smem();
        }
        __syncwarp();
        KSTAMP(true, 188);
        bar_arrive(0, 384);
        CLUSTER_ARRIVE();
        }
            auto pf_w = [&](int r) { pf_l2(padd(P.Wg, (128 * r + b) * 3072), 3072); pf_l2(padd(P.Wu, (128 * r + b) * 3072), 3072); };
            auto load_w = [&](int m) {
                mbar_expect(BAR(B_WF + (m & 3)), 16384);
                tma3d_mc(sb + WR + (m & 3) * 16384 + rank * 8192, &M.w[0] + rank, m * 32, js * 3, BAR(B_WF + (m & 3)));
            };
            if (elect()) {
                KSTAMP(true, 185);
                static_for<0, NLD>([&](auto I) {
                    constexpr uint32_t e = c_sched.ld[I.value], n = e & 15, kind = (e >> 4) & 15, prev = I.value ? (c_sched.ld[I.value ? I.value - 1 : 0] >> 4) & 15 : 0;
                    if constexpr (e != 0) {
                        if (kind < 3) mbar_expect(BAR(5 * kind + n), kind ? 4096 + 16 * (kind == 1) : KVP + 256);
                        if (kind > 3 && prev <= 3) mbar_wait(BAR(B_CR), 0);
                        if (kind == 4 && n == 0) mbar_wait(BAR(B_FF), 0);
                        wait_clock(clk0, SCH(ld[I.value]) >> 8);
                        if (kind == 0) load_kv(n);
                        if (kind == 1) load_h(n);
                        if (kind == 2) tma4d(sb + QS + n * 4096, &M.q, n * 128 + cg * 32, 248 - 8 * tb, BAR(B_Q + n));
                        if (kind == 3) pf_w(n);
                        if (kind == 4) {
                            const int tl = tile - (tile == 15), t3 = (tl * 11) >> 5, cm = 2 * (tl - 3 * t3) + (n >> 1);
                            tma3d(sb + UST + n * 8192, cm >= 3 ? &M.w[3] : &M.w[2], 0, t3 * 128 + (n & 1) * 64, js * 3 + cm - 3 * (cm >= 3), BAR(B_UF));
                        }
                        if (kind == 8) { if (n & 2) mbar_wait(BAR(B_FF - 1 + n), 0); load_w(n); }
                    }
                });
                STAMP(126);
                _Pragma("unroll 1") for (int m = 4; m < 20; m++) {
                    mbar_wait(BAR(B_WE + (m & 3)), ~(m >> 2) & 1);
                    load_w(m);
                    if (m == 12) pf_l2(padd(P.Wd, b * 15360), 15360);
                }
                #pragma unroll
                for (int it = 0; it < 10; it++) {
                    if (it < 4 || !(it & 1)) mbar_wait(BAR(B_WE + (it < 4 ? it : (it >> 1) - 2)), it >= 4);
                    mbar_expect(BAR(w2_bar(it)), 16384);
                    tma3d_mc(sb + w2_at(it) + rank * 8192, &M.w[2] + rank, it * 64, js * 3 + 2, BAR(w2_bar(it)));
                }
                #pragma unroll
                for (int m = 0; m < 9; m++) mbar_expect(BAR(B_AF + m), 16384);
                const char* hp[3];
                #pragma unroll
                for (int m = 0; m < 3; m++) hp[m] = SC(hh, (tile * 24 + (kh * 4 + m + (m >= dq)) * 3) * 16384);
                const uint32_t* fl = CNT(C_HH + tile * 2 + kh);
                const uint32_t target = lds32(sb + HT);
                sts128(sb + TAB1, target - 1, target - 1, target - 1, 0); sts128(sb + TAB1 + 16, target - 1, target - 1, target - 1, 0);
                #pragma unroll
                for (int c = 0; c < 3; c++) {
                    #pragma unroll
                    for (int m = 0; m < 3; m++) {
                        if (c != 1 || m == 0) wait_dual(fl, sb + TAB1, 4 * c, target, BAR(c == 0 ? B_WE + ((m + 3) & 3) : c == 1 ? B_S0 : B_HE + m), c + m == 0);
                        STAMPIF(m == 0, 170 + c); STAMPIF(m == 2, 173 + c);
                        bulk_g2s(sb + G2A + ((c & 1) ? (m ? m - 1 : 4) : m ? m + 1 : 5) * 16384, hp[m] + (c ^ (c < 2)) * 16384, 16384, BAR(B_AF + 3 * c + m));
                    }
                }
                asm volatile("cp.async.wait_all;" ::: "memory");
            }
            PROF_EXIT();
            return;
        }
        if (warp == 8) {
            const int kind = (lane * 13) >> 7, pr = (lane >> 1) - 5 * kind;
            if (lane == 0) asm volatile("ld.relaxed.gpu.global.u32 %0, [%1];" : "=r"(epoch) : "l"(CNT(C_ZO)) : "memory");
            const uint32_t base = (C_KV + (bc >> 5)) | (C_Y + cg) << 8 | (C_Z + tile) << 16 | (C_HH - 256 + tile * 2 + kh) << 24;
            const uint32_t* cp = CNT((lane & 1) * 32 + ((base >> (8 * kind)) & 255) + (pr << (kind == 2 ? 6 : 2)) + (lane >= 30) * 256);
            asm volatile("cp.async.cg.shared.global [%0], [%1], 16;" :: "r"(sb + PS + lane * 16), "l"(cp) : "memory");
            sts32(sb + PRE + lane * 4, 0);
            if (lane == 0) sts32(sb + HT + 4, (epoch >> 7) + 1);
            KSTAMP(true, 187);
            CLUSTER_ARRIVE();
            bar_sync(0, 384);
            KSTAMP(true, 191);
            asm volatile("barrier.cluster.wait.aligned;\n cp.async.wait_all;" ::: "memory");
            const uint32_t slot = sb + PS + lane * 16, goal = (lds32(slot) | 127) + 1;
            if (lane == 31) { sts32(sb + HT, goal); mbar_arrive(BAR(B_CR)); }
            KSTAMP(true, 5);
            const int r = pr;
            const char* src = kind == 0 ? SC(kvT, (bc + 128 * r) * 4096) : kind == 1 ? SC(yB, ((r * 4 + cg) * 32 + tb) * 4096) : SC(z, (tile * 10 + lane - 20) * 16384);
            const uint32_t dst = sb + (kind == 0 ? x_at(r) : kind == 1 ? YS + (r - 3 * (r >= 3)) * 4096 : (lane - 20) * 16384);
            const uint32_t bytes = kind == 2 ? 16384 : 4096, full = BAR(kind == 2 ? B_AF - 20 + lane : B_XF + (lane >> 1)), pre = sb + PRE + (lane >> 1) * 8;
            uint32_t need = lane >= 30 ? ~0u : lane < 16 ? 0 : (0x3811822 >> (2 * (lane & 14))) & 15;
            const uint32_t lbit = __shfl_sync(~0u, (kind == 2 || (kind < 2 && !(lane & 1))) ? 1u << lane : 0u, lane), pbit = __shfl_sync(~0u, 3u << (lane & 30), lane);
            uint32_t todo = 0x15555555, it = 0;
            if (lbit) mbar_expect(full, bytes);
            if (lane == 0) mbar_expect(BAR(B_UF), 32768);
            epoch = __shfl_sync(~0u, goal, 0) >> 7;
            int nx = 0;
            __syncwarp();
            while (todo) {
                uint32_t hit;
                asm volatile("{ .reg .pred p, q, t; .reg .u32 c, o, v;\n LAB_EV:\n ld.volatile.shared.v2.u32 {c, o}, [%4]; ld.volatile.shared.u32 v, [%2];\n"
                             " mbarrier.test_wait.parity.shared::cta.b64 t, [%6], 0; add.u32 %1, %1, 1;\n"
                             " sub.u32 v, v, %7; setp.ge.s32 p|q, v, 0; setp.gt.and.u32 q, o, %8, q; @q cp.async.cg.shared.global [%2], [%3], 16; setp.eq.and.u32 p, c, %5, p; setp.ge.or.u32 p, %1, 400000, p;\n"
                             " vote.sync.ballot.b32 %0, p, 0xffffffff; setp.ne.or.u32 p, %0, 0, t;\n @!p bra.uni LAB_EV;\n }"
                             : "=r"(hit), "+r"(it) : "r"(slot), "l"(cp), "r"(pre), "r"(need), "r"(BAR(nx < 5 && !(todo & SCH(xd)) ? B_FD + nx : B_X1)), "r"(goal), "r"(need >> 4) : "memory");
                if (hit) {
                    KSTAMP(!(lane & 1) && (hit & pbit) && lane < 30, 216 + (lane >> 1));
                    if (hit & pbit) { need = ~0u; if (lbit) bulk_g2s(dst, src, bytes, full); }
                    todo &= ~(hit | (hit >> 1));
                    __syncwarp();
                    if ((hit & (3 * CSM)) && !(todo & CSM)) {
                        float2 sc[4];
                        ll_read2<2, 2560, 2, 256>(SC(mod, (1920 + (((tile - (tile == 15)) * 11) >> 5) * 128 + 2 * lane) * 4), epoch, sc);
                        #pragma unroll
                        for (int n = 0; n < 4; n++) { const float one = n >> 1;
                            sts32(sb + CS_TAB + ((lane >> 2) + 8 * (n & 1)) * 32 + (lane & 3) * 4 + (n < 2) * 16, pack2(bfround(sc[n].x) + one, bfround(sc[n].y) + one)); }
                        fence_async_smem(); __syncwarp(); mbar_arrive_if(BAR(B_UF), lane == 0);
                        KSTAMP(true, 52);
                    }
                } else {
                    if (elect()) {
                        tma4d_st(&M.o1, sb + QS + nx * 4096, nx * 128 + cg * 32, 248 - 8 * tb);
                        if (nx == 4) { asm volatile("cp.async.bulk.commit_group;\n cp.async.bulk.wait_group.read 0;" ::: "memory"); pre_add(sb + PRE + 112, true); }
                    }
                    __syncwarp();
                    nx++;
                }
            }
            asm volatile("cp.async.wait_all;" ::: "memory");
            __syncwarp();
            mbar_arrive_if(BAR(B_UD), lane == 0);
        } else {
            bar_arrive(0, 384);
            if (elect()) {
                if (warp == 10) { _Pragma("unroll") for (int i = B_XF; i < 47; i++) if (i != B_CR) mbar_init(BAR(i), bar_count(i)); }
                else { _Pragma("unroll") for (int i = 47; i < NBARS; i++) mbar_init(BAR(i), bar_count(i)); }
                asm volatile("fence.mbarrier_init.release.cluster;" ::: "memory");
            }
            if (lane < 24) sts128(sb + PB - (warp & 1) * 32768 + (lane & 3) * PP + 4096 + (lane >> 2) * 16, 0, 0, 0, 0);
            if (lane < 12) sts128(sb + (lane < 5 ? h_at(lane) : lane == 5 ? HO0 : lane == 6 ? HO1 : x_at(lane - 7) + 4096), 0, 0, 0, 0);
            fence_async_smem();
            KSTAMP(true, 180);
            CLUSTER_ARRIVE();
            asm volatile("barrier.cluster.wait.aligned;" ::: "memory");
            if (warp == 11 && lane < 11) asm volatile("prefetch.global.L2 [%0];" :: "l"(padd(&M.q, lane * 128)) : "memory");
            mbar_wait(BAR(B_CR), 0);
            epoch = __shfl_sync(~0u, lds32(sb + HT), 0) >> 7;
            const int wf = warp - 10, c = lane >> 2, run = 4 * wf + (lane & 3);
            auto mod_fetch = [&](int n, int lane) { asm volatile("cp.async.cg.shared.global [%0], [%1], 16;" :: "r"(sb + RAW + lane * 16), "l"(SC(mod, (((lane >> 3) + (lane >= 24)) * 640 + 128 * n + 32 * cg + (lane & 7) * 4) * 4)) : "memory"); };
            auto mod_put = [&](int n, int lane) {
                uint32_t mv[4];
                _Pragma("unroll 1") for (int it = 0; it < 20000; it++) {
                    asm volatile("cp.async.wait_all;" ::: "memory");
                    __syncwarp();
                    #pragma unroll
                    for (int i = 0; i < 4; i++) mv[i] = lds32(sb + RAW + i * 128 + lane * 4);
                    if (!__any_sync(~0u, (((mv[0] ^ epoch) | (mv[1] ^ epoch) | (mv[2] ^ epoch) | (mv[3] ^ epoch)) & 7) != 0)) break;
                    if (it) asm volatile("nanosleep.u32 150;");
                    mod_fetch(n, lane);
                }
                const float ga = bfround(__uint_as_float(mv[2])), a0 = ga * bfround(__uint_as_float(mv[0])), a1 = ga * bfround(bfround(__uint_as_float(mv[1])) + 1.f), c1 = bfround(__uint_as_float(mv[3])) + 1.f;
                if (n) bar_sync(4, 64);
                asm volatile("st.shared.v2.b32 [%0], {%1, %2};" :: "r"(sb + CT + (lane & 7) * 32 + (lane >> 3) * 8), "r"(pack2(a0, a1)), "r"(pack2(c1, c1)) : "memory");
                __syncwarp();
                mbar_arrive_if(BAR(B_YF + n), lane == 0);
                STAMP(150 + n);
            };
            const int qrow = 63 - 16 * (lane >> 3) - 8 * wf - (lane & 7);
            uint32_t qa = sb + QS + qrow * 64 + (((qrow >> 1) & 3) << 4);
            float s1 = 0.f, s2 = 0.f;
            auto row_stats = [&](uint32_t a) {
                float st[4] = {s1, s2, 0.f, 0.f};
                uint4 v[4];
                #pragma unroll
                for (int i = 0; i < 4; i++) v[i] = lds128(a ^ (i << 4));
                #pragma unroll
                for (int i = 0; i < 16; i++) {
                    const uint32_t u = (&v[i >> 2].x)[i & 3]; const float a0 = bflo(u), a1 = bfhi(u);
                    vadd(st[0], a0); vfma(st[1], a0, a0); vadd(st[2], a1); vfma(st[3], a1, a1);
                    if ((i & 3) == 3) yield();
                }
                s1 = st[0] + st[2]; s2 = st[1] + st[3];
            };
            auto put_stats = [&](uint32_t off) { ll_write1(padd(P.scr, off + (tb * 4 + cg) * 512 + (((qa - sb) >> 3) & 504)), __uint_as_float(tagged(s1, epoch)), __float_as_uint(s2)); };
            _Pragma("unroll 1") for (int r = 0; r < 5; r++) {
                if (r == 4 && wf) mod_fetch(0, lane);
                mbar_wait(BAR(B_Q + r), 0);
                STAMPIF(wf == 0 && r == 4, 62);
                row_stats(qa + r * 4096);
            }
            put_stats(offsetof(Scratch, st1));
            uint32_t tp;
            asm volatile("mov.u32 %0, %%clock;" : "=r"(tp));
            STAMPIF(wf == 0, 40);
            if (wf) mod_put(0, lane);
            s1 = s2 = 0.f;
            wait_clock(tp, SCH(spin));
            {
                const char* sp = SC(st1, (tb * 256 + 63 - 16 * (c >> 1) - (c & 1) - 2 * run) * 8);
                float s, ss;
                _Pragma("unroll 1") for (int it = 0; it < 20000; it++) {
                    uint2 v[4];
                    #pragma unroll
                    for (int i = 0; i < 4; i++) asm volatile("{ .reg .b64 x; ld.relaxed.gpu.global.b64 x, [%2]; mov.b64 {%0, %1}, x; }" : "=r"(v[i].x), "=r"(v[i].y) : "l"(sp + i * 512) : "memory");
                    s = (__uint_as_float(v[0].x) + __uint_as_float(v[1].x)) + (__uint_as_float(v[2].x) + __uint_as_float(v[3].x));
                    ss = (__uint_as_float(v[0].y) + __uint_as_float(v[1].y)) + (__uint_as_float(v[2].y) + __uint_as_float(v[3].y));
                    if (!__any_sync(~0u, (((v[0].x ^ epoch) | (v[1].x ^ epoch) | (v[2].x ^ epoch) | (v[3].x ^ epoch)) & 7) != 0)) break;
                    asm volatile("nanosleep.u32 100;");
                }
                const float mu = s * (1.f / D_), rs = bfround(rsqrtf(fmaxf(ss * (1.f / D_) - mu * mu, 0.f) + 1e-5f));
                const uint32_t mr = pack2(-mu * rs, rs);
                asm volatile("st.shared.u16 [%0], %1; st.shared.u16 [%0+128], %2;" :: "r"(sb + MR + run * 16 + c * 2), "h"((uint16_t)mr), "h"((uint16_t)(mr >> 16)) : "memory");
                STAMPIF(wf == 0, 41);
            }
            const int lw = __shfl_sync(~0u, lane, lane);
            char* zp = SC(z, ((tb >> 1) * 10 + (cg >> 1)) * 16384 + (tb & 1) * 8192 + (cg & 1) * 4096 + wf * 2048 + c * 64 + (((lane ^ (c >> 1)) & 3) << 4));
            _Pragma("unroll 1") for (int r = 0; r < 5; r++) {
                const int lane = lw | P.zero[r];
                const int c = lane >> 2, run = 4 * wf + (lane & 3);
                const int r3 = r - 3 * (r >= 3);
                const uint32_t yo = c * 128 + ((run ^ ((c & 1) << 2)) << 4), ya = sb + YS + r3 * 4096 + yo, ca = sb + CT + c * 32;
                __syncwarp();
                uint32_t x[16];
                auto ldx = [&](int h) { asm volatile("ldmatrix.sync.aligned.m8n8.x4.trans.shared.b16 {%0,%1,%2,%3}, [%4];" : "=r"(x[4 * h]), "=r"(x[4 * h + 1]), "=r"(x[4 * h + 2]), "=r"(x[4 * h + 3]) : "r"(qa ^ (h << 4)) : "memory"); };
                auto stx = [&](int h) { asm volatile("stmatrix.sync.aligned.m8n8.x4.trans.shared.b16 [%0], {%1,%2,%3,%4};" :: "r"(qa ^ (h << 4)), "r"(x[4 * h]), "r"(x[4 * h + 1]), "r"(x[4 * h + 2]), "r"(x[4 * h + 3]) : "memory"); };
                ldx(0); ldx(1);
                const uint4 mu = lds128(sb + MR + run * 16), rs = lds128(sb + MR + 128 + run * 16);
                void* hp = CNT(C_Z + 64 * r + (tb >> 1) + 32 * (lane & 1));
                EARLY(hint_cnt<8>(hp, lane < 2));
                mbar_wait(BAR(B_YF + r), 0);
                STAMPIF(wf == 0, 155 + r);
                const bool mine = (r & 1) == wf && r < 4;
                uint4 y[2], cs;
                _Pragma("unroll 1") for (int tries = 0;; tries++) {
                    y[0] = lds128(ya); y[1] = lds128(ya + 1024); cs = lds128(ca);
                    uint32_t bad;
                    asm("{ .reg .b32 a, b; lop3.b32 a, %1, %2, %5, 0x7e; lop3.b32 b, %3, %4, %5, 0x7e; lop3.b32 %0, a, b, 1, 0xa8; }" : "=r"(bad) : "r"(y[0].x), "r"(y[1].x), "r"(lds32(ya + 2048)), "r"(lds32(ya + 3072)), "r"(epoch));
                    if (!__any_sync(~0u, bad) || tries) break;
                    repair_tile<4, 1024, 2048>(ya, SC(yB, ((r * 4 + cg) * 32 + tb) * 4096) - (sb + YS + r3 * 4096), epoch);
                    STAMP(125);
                }
                #pragma unroll
                for (int h = 0; h < 4; h++) {
                    uint32_t* xh = x + 4 * h; uint4& yh = y[h & 1];
                    #pragma unroll
                    for (int j = 0; j < 4; j++)
                        asm("{ .reg .b16 l, h; .reg .b32 a0, a1, n; mov.b32 {l, h}, %4; mov.b32 a0, {l, l}; mov.b32 a1, {h, h}; fma.rn.bf16x2 n, %0, %2, %3; fma.rn.bf16x2 n, n, a1, a0; fma.rn.bf16x2 %0, n, %1, %0; mul.rn.bf16x2 %1, %0, %5; }"
                            : "+r"(xh[j]), "+r"((&yh.x)[j]) : "r"((&rs.x)[j]), "r"((&mu.x)[j]), "r"((h & 1) ? cs.z : cs.x), "r"((h & 1) ? cs.w : cs.y));
                    (&yh.x)[h] = tagbit((&yh.x)[h], epoch);
                    stg_v4(zp + h * 512, yh.x, yh.y, yh.z, yh.w);
                    if (h < 2) { stx(h); yh = lds128(ya + 2048 + h * 1024); ldx(h + 2); }
                    if (h == 1) { cs = lds128(ca + 16); if (mine) mod_fetch(r + 1, lane); }
                }
                __syncwarp();
                LATE(hint_cnt<8>(hp, lane < 2));
                pre_add(sb + PRE + 84 + r * 8 - 20 * (lane & 1), lane < 1 + (r < 2));
                KSTAMP(wf == 0, 160 + r);
                stx(2); stx(3);
                __syncwarp();
                if (!mine && r < 4) bar_arrive(4, 64);
                if (r == 4) { fence_async_smem(); __syncwarp(); mbar_arrive_if(BAR(B_FD + 4), lane == 0); }
                row_stats(qa);
                if (mine) mod_put(r + 1, lane);
                if (r < 4) { fence_async_smem(); __syncwarp(); mbar_arrive_if(BAR(B_FD + r), lane == 0); }
                qa += 4096; zp += 32768;
            }
            put_stats(offsetof(Scratch, st2));
            pre_add(sb + PRE + 112, lane == 0);
            __syncwarp();
            STAMPIF(wf, 53);
        }
        {
            mbar_wait(BAR(B_UD), 0);
            const int n = warp - 9 + (warp == 8);
            _Pragma("unroll 1") for (int h = 0; h < 2; h++) {
                const char* up = SC(ut, (h * 1536 + js * 192 + n * 64 + 2 * lane) * 8);
                uint4 v[5];
                _Pragma("unroll 1") for (int it = 0; it < 20000; it++) {
                    uint32_t bad = 0;
                    #pragma unroll
                    for (int i = 0; i < 5; i++) v[i] = ldg_rlx128(up + i * 24576);
                    #pragma unroll
                    for (int i = 0; i < 5; i++) bad |= (v[i].x ^ epoch) | (v[i].z ^ epoch);
                    if (!__any_sync(~0u, (bad & 7) != 0)) break;
                    asm volatile("nanosleep.u32 100;");
                }
                float f[4];
                #pragma unroll
                for (int j = 0; j < 4; j++) f[j] = (__uint_as_float((&v[0].x)[j]) + __uint_as_float((&v[1].x)[j])) + (__uint_as_float((&v[2].x)[j]) + __uint_as_float((&v[3].x)[j])) + __uint_as_float((&v[4].x)[j]);
                const uint32_t ta = sb + TAB1 + ((n == 2 ? 32 + h * 8 : n * 8 + h * 16) + (lane >> 2)) * 48 + (lane & 3) * 4, th2 = pack2(f[1], f[3]);
                sts32(ta, pack2(f[0], f[2])); sts32(ta + 16, th2); sts32(ta + 32, pack2(f[1] - bflo(th2), f[3] - bfhi(th2)));
            }
            if (lane < 20) sts32(sb + TAB1 + 48 * 48 + lane * 4, 0);
            fence_async_smem();
            __syncwarp();
            if (lane == 0) mbar_arrive(BAR(B_T1));
            STAMPIF(warp == 10, 61);
        }
        if (warp == 11) {
            char* hc = paddv(P.scr, (C_HH + tile * 2 + kh + 32 * (lane & 1)) * 128);
            #pragma unroll
            for (int c = 0; c < 3; c++) { EARLY(hint_cnt<32>(hc + 4 * c, lane < 2)); mbar_wait(BAR(B_HD + (c & 1)), c >> 1); LATE(hint_cnt<32>(hc + 4 * c, lane < 2)); STAMP(176 + c); }
            float2 gbv[3];
            ll_read2<1, 0, 3, 192>(SC(mod, (5 * 640 + dq * 160 + 2 * lane) * 4), epoch, gbv);
            #pragma unroll
            for (int n = 0; n < 3; n++) sts32(sb + GBT + (lane & 3) * 80 + ((lane >> 2) + 6 * n) * 4, pack2(gbv[n].x, gbv[n].y));
            poll_cnt((uint32_t*)paddv(P.scr, C_ZO * 128 + (lds32(sb + HT) & 127)), epoch << 7);
            fence_async_glob();
            __syncwarp();
            mbar_arrive_if(BAR(B_X1), lane == 0);
        } else if (warp == 8) {
            if (elect()) {
                asm volatile("cp.async.bulk.wait_group 0;" ::: "memory");
                fence_async_glob();
                signal_cnt((uint32_t*)paddv(P.scr, C_ZO * 128 + (lds32(sb + HT) & 127)), 1);
            }
            __syncwarp();
            uint32_t rtp = 0;
            mbar_wait(BAR(B_WX), 0);
            _Pragma("unroll 1") for (int v = 0; v < 9; v++) {
                const int c = (v * 11) >> 5, m = v - 3 * c;
                const uint32_t ok = BAR(B_G2F + m + (c == 0 ? 2 : c == 1 ? 0 : 3)), dst = sb + G2A + ((c & 1) ? (m ? m - 1 : 4) : m ? m + 1 : 5) * 16384, a = dst + (lane >> 3) * 516 + (lane & 7) * 16;
                if (c) mbar_wait(ok, 0);
                mbar_wait(BAR(B_AF + v), 1);
                _Pragma("unroll 1") for (int it = 0; it < 1000; it++) {
                    uint32_t w[32], bad = 0;
                    #pragma unroll
                    for (int i = 0; i < 32; i++) w[i] = lds32(a + (i >> 2) * 2048 + (i & 3) * 128);
                    #pragma unroll
                    for (int i = 0; i < 32; i += 4)
                        asm("{ .reg .b32 a, b; lop3.b32 a, %1, %2, %5, 0x7e; lop3.b32 b, %3, %4, %5, 0x7e; lop3.b32 %0, %0, a, b, 0xfe; }" : "+r"(bad) : "r"(w[i]), "r"(w[i + 1]), "r"(w[i + 2]), "r"(w[i + 3]), "r"(epoch));
                    if (!__any_sync(~0u, bad & 1)) break;
                    if (elect()) { mbar_expect(BAR(B_RT), 16384); bulk_g2s(dst, SC(hh, (tile * 24 + (kh * 4 + m + (m >= dq)) * 3 + (c ^ (c < 2))) * 16384), 16384, BAR(B_RT)); }
                    mbar_wait(BAR(B_RT), rtp);
                    rtp ^= 1;
                    STAMP(122);
                }
                mbar_arrive_if(ok, lane == 0);
            }
        } else if (elect()) {
            {
                int g = 0, c = 0, m = 0;
                _Pragma("unroll 1") for (int n = 0; n < 12; n++) {
                    const uint32_t st = sb + g2b_at(g) + rank * 10240, f = BAR(B_G2F + g);
                    mbar_wait_cluster(BAR(B_G2E + g), n >= 6);
                    mbar_expect(f, 20480);
                    if (n < 2 || n == 5) { mbar_arrive(f); tma3d_mc(st, &M.wn, (js * 3 + (n < 2 ? n : 2)) * 64 + rank * 32, dq * 5, f); }
                    else {
                        tma5d_mc(st, &M.wd, ((kh * 4 + m + (m >= dq)) * 3 + (c ^ (c < 2))) * 8 + rank * 4, dq * 5, f);
                        if (++m == 3) { m = 0; c++; }
                    }
                    g = g == 5 ? 0 : g + 1;
                }
            }
        }
        PROF_EXIT();
    }
}

typedef CUresult (*EncodeFn)(CUtensorMap*, CUtensorMapDataType, cuuint32_t, void*, const cuuint64_t*, const cuuint64_t*, const cuuint32_t*, const cuuint32_t*,
                             CUtensorMapInterleave, CUtensorMapSwizzle, CUtensorMapL2promotion, CUtensorMapFloatOOBfill);
void enc(EncodeFn fn, CUtensorMap* m, const void* ptr, int rank, const cuuint64_t* dims, const cuuint64_t* strides, const cuuint32_t* box, CUtensorMapSwizzle sw,
         CUtensorMapL2promotion pr = CU_TENSOR_MAP_L2_PROMOTION_L2_128B) {
    cuuint32_t es[5] = {1, 1, 1, 1, 1};
    fn(m, CU_TENSOR_MAP_DATA_TYPE_BFLOAT16, rank, (void*)ptr, dims, strides, box, es, CU_TENSOR_MAP_INTERLEAVE_NONE, sw, pr, CU_TENSOR_MAP_FLOAT_OOB_FILL_NONE);
}
#define PROMO CU_TENSOR_MAP_L2_PROMOTION_L2_128B
}

extern "C" void kernel_launch(void* const* d_in, const int* in_sizes, int n_in, void* d_out, int out_size) {
    void* fnp = nullptr; cudaDriverEntryPointQueryResult st;
    cudaGetDriverEntryPoint("cuTensorMapEncodeTiled", &fnp, cudaEnableDefault, &st);
    EncodeFn fn = (EncodeFn)fnp;
    void* scr;
    cudaGetSymbolAddress(&scr, g_s);
    Maps M; Ptrs P;
    P.k = (const char*)d_in[1]; P.v = (const char*)d_in[2]; P.shift = (const char*)d_in[3];
    P.ssm = (const char*)d_in[4]; P.ssmD = (const char*)d_in[5]; P.Wg = (const char*)d_in[7]; P.Wu = (const char*)d_in[8];
    P.Wd = (const char*)d_in[9]; P.c = (const char*)d_in[10]; P.scr = (char*)scr;
    for (int i = 0; i < 8; i++) { P.zero[i] = 0; P.wl[i] = i < 5 ? c_sched.wl[i] : 0; }
    { cuuint64_t d[3] = {640, 256, 8}, s[2] = {8 * 1280, 1280}; cuuint32_t b1[3] = {32, 9, 8}, b2[3] = {32, 8, 8};
      enc(fn, &M.k, P.k, 3, d, s, b1, CU_TENSOR_MAP_SWIZZLE_64B, PROMO); enc(fn, &M.v, P.v, 3, d, s, b2, CU_TENSOR_MAP_SWIZZLE_64B, PROMO); }
    { cuuint64_t d[4] = {640, 2, 256, 4}, s[3] = {1280, 8 * 1280, 2 * 1280}; cuuint32_t b1[4] = {32, 2, 8, 4};
      enc(fn, &M.q, d_in[0], 4, d, s, b1, CU_TENSOR_MAP_SWIZZLE_64B, PROMO); enc(fn, &M.o1, d_out, 4, d, s, b1, CU_TENSOR_MAP_SWIZZLE_64B, PROMO); }
    { cuuint64_t d[3] = {64, 640, 24}, s[2] = {3072, 128}; cuuint32_t bx[2][3] = {{64, 32, 2}, {64, 64, 1}};
      for (int i = 0; i < 4; i++) enc(fn, &M.w[i], (i & 1) ? P.Wu : P.Wg, 3, d, s, bx[i >> 1], CU_TENSOR_MAP_SWIZZLE_128B); }
    { cuuint64_t d[5] = {32, 2, 192, 4, 20}, s[4] = {1280, 8 * 1280, 2 * 1280, 64}; cuuint32_t b1[5] = {32, 2, 4, 4, 5};
      enc(fn, &M.wd, P.Wd, 5, d, s, b1, CU_TENSOR_MAP_SWIZZLE_64B); }
    { cuuint64_t d[3] = {32, 1536, 20}, s[2] = {1280, 64}; cuuint32_t b1[3] = {32, 32, 5};
      enc(fn, &M.wn, P.Wd, 3, d, s, b1, CU_TENSOR_MAP_SWIZZLE_64B); }
    { cuuint64_t d[2] = {3840, 640}, s[1] = {7680}; cuuint32_t b1[2] = {64, 160};
      enc(fn, &M.wm, d_in[11], 2, d, s, b1, CU_TENSOR_MAP_SWIZZLE_128B); }
    { cuuint64_t d[2] = {640, 2048}, s[1] = {1280}; cuuint32_t b1[2] = {64, 16}, b2[2] = {32, 16};
      enc(fn, &M.out, d_out, 2, d, s, b1, CU_TENSOR_MAP_SWIZZLE_128B); enc(fn, &M.ou2, d_out, 2, d, s, b2, CU_TENSOR_MAP_SWIZZLE_64B); }
    cudaFuncSetAttribute(fused_kernel, cudaFuncAttributeMaxDynamicSharedMemorySize, SMEM_BYTES);
    fused_kernel<<<132, 384, SMEM_BYTES>>>(P, M);
}
```
